```python
import torch

def _softmax(x, axis=-1):
    return torch.softmax(x, dim=axis)
def _gelu(x):
    return torch.nn.functional.gelu(x, approximate="tanh")
def _silu(x):
    return torch.nn.functional.silu(x)
def _sigmoid(x):
    return torch.sigmoid(x)
def _layernorm(x, axis=-1, eps=1e-5):
    m = x.mean(dim=axis, keepdim=True)
    v = x.var(dim=axis, keepdim=True, unbiased=False)
    return (x - m) / torch.sqrt(v + eps)
def _scatter_add(tgt, idx, src, axis=0):
    return tgt.clone().index_add_(axis, idx, src)
def _segment_sum(src, seg, n):
    out = torch.zeros((n,) + src.shape[1:], dtype=src.dtype)
    return out.index_add_(0, seg, src)
def _pad(x, pw):
    flat = tuple(v for pair in reversed(pw) for v in pair)
    return torch.nn.functional.pad(x, flat)

kernel_name = 'recurrent_scan__gqa_block_cached__glu_gated_swiglu__prompt'

def setup_inputs():

    _w = (lambda a: (lambda t: t.to(torch.bfloat16) if t.is_floating_point() else t)(torch.as_tensor(a)))
    def _A_setup():
        B, Sq, D = 1, 2048, 576
        Hq, Hkv, Sk, Dh = 32, 16, 2048, 128
        assert Hq % Hkv == 0, (Hq, Hkv)
        return {
            "x": _w((lambda *s: torch.randn(*s, dtype=torch.bfloat16) * 0.05)(B, Sq, D)),
            "k_cache": _w((lambda *s: torch.randn(*s, dtype=torch.bfloat16) * 1.6)(B, Hkv, Sk, Dh)),
            "v_cache": _w((lambda *s: torch.randn(*s, dtype=torch.bfloat16) * 1.6)(B, Hkv, Sk, Dh)),
            "wq": _w((lambda *s: torch.randn(*s, dtype=torch.bfloat16) * 1.6)(D, Hq * Dh) * (D ** -0.5)),
            "wo": _w((lambda *s: torch.randn(*s, dtype=torch.bfloat16) * 1.6)(Hq * Dh, D) * ((Hq * Dh) ** -0.5)),
        }
    _A_in = _A_setup()

    def _B_setup():
        B, S, D, F = 1, 2048, 576, 4608
        return {
            "x": _w((lambda *s: torch.randn(*s, dtype=torch.bfloat16) * 0.05)(B, S, D)),
            "w1": _w((lambda *s: torch.randn(*s, dtype=torch.bfloat16) * 0.2)(D, F) * (2.0 / D) ** 0.5),
            "w3": _w((lambda *s: torch.randn(*s, dtype=torch.bfloat16) * 0.2)(D, F) * (2.0 / D) ** 0.5),
            "w2": _w((lambda *s: torch.randn(*s, dtype=torch.bfloat16) * 0.2)(F, D) * (2.0 / F) ** 0.5),
        }
    _B_in = _B_setup()

    return {
        "A_x": _A_in["x"],
        "A_k_cache": _A_in["k_cache"],
        "A_v_cache": _A_in["v_cache"],
        "A_wq": _A_in["wq"],
        "A_wo": _A_in["wo"],
        "B_x": _B_in["x"],
        "B_w1": _B_in["w1"],
        "B_w3": _B_in["w3"],
        "B_w2": _B_in["w2"],
    }

def reference(A_x, A_k_cache, A_v_cache, A_wq, A_wo, B_x, B_w1, B_w3, B_w2):
    def _A_ref(x, k_cache, v_cache, wq, wo):
        B, Sq, D = x.shape
        Hq, Dh = 32, 128
        Hkv = k_cache.shape[1]
        rep = Hq // Hkv
        q = (lambda x, *d: x.permute(*d))((x @ wq).reshape(B, Sq, Hq, Dh), 0, 2, 1, 3)
        k = (lambda x, n, axis: torch.repeat_interleave(x, n, dim=axis))(k_cache, rep, axis=1)
        v = (lambda x, n, axis: torch.repeat_interleave(x, n, dim=axis))(v_cache, rep, axis=1)
        scores = torch.einsum("bhqd,bhkd->bhqk", q, k) * (Dh ** -0.5)
        p = _softmax(scores, axis=-1)
        o = torch.einsum("bhqk,bhkd->bhqd", p, v)
        return (lambda x, *d: x.permute(*d))(o, 0, 2, 1, 3).reshape(B, Sq, Hq * Dh) @ wo

    def _B_ref(x, w1, w3, w2):
        gate = torch.einsum("bsd,df->bsf", x, w1)
        up = torch.einsum("bsd,df->bsf", x, w3)
        h = _silu(gate) * up
        out = torch.einsum("bsf,fd->bsd", h, w2)
        return out

    x = A_x
    xn = _layernorm(x, axis=-1)
    s = _A_ref(xn, A_k_cache, A_v_cache, A_wq, A_wo)
    g = _silu(_B_ref(xn, B_w1, B_w3, B_w2))
    return x + s * g
```

```cpp
#include <cuda_runtime.h>
#include <cuda_bf16.h>
#include <cuda.h>
#include <stdint.h>

namespace fk {

constexpr int SEQ = 2048, DM = 576, FF = 4608;
constexpr int NSLOT = 14;
constexpr int SLOT_BYTES = 16384;
constexpr int RING_BYTES = NSLOT * SLOT_BYTES;
constexpr int SMEM_BYTES = RING_BYTES + 512;
constexpr int NCTA = 128;

__device__ uint4 g_qo[NCTA * 4 * 2 * 8 * 128];
__device__ uint4 g_h[NCTA * 2 * 36 * 128];
__device__ float4 g_S[16 * 2 * 72 * 128];
__device__ float4 g_G[16 * 2 * 72 * 128];
__device__ unsigned int g_cntZ[16 * 32];
__device__ unsigned int g_cntD[16 * 32];

__device__ __forceinline__ uint32_t smem_u32(const void* p) { return (uint32_t)__cvta_generic_to_shared(p); }
__device__ __forceinline__ uint64_t gtime() { uint64_t t; asm volatile("mov.u64 %0, %globaltimer;" : "=l"(t)); return t; }

__device__ __forceinline__ void mbar_init(uint32_t bar, uint32_t cnt) {
  asm volatile("mbarrier.init.shared::cta.b64 [%0], %1;" ::"r"(bar), "r"(cnt) : "memory");
}
__device__ __forceinline__ bool mbar_try(uint32_t bar, uint32_t parity) {
  uint32_t ok;
  asm volatile("{\n.reg .pred p;\nmbarrier.try_wait.parity.shared::cta.b64 p, [%1], %2;\nselp.u32 %0, 1, 0, p;\n}"
               : "=r"(ok) : "r"(bar), "r"(parity) : "memory");
  return ok != 0;
}
__device__ __forceinline__ bool mbar_try_cluster(uint32_t bar, uint32_t parity) {
  uint32_t ok;
  asm volatile("{\n.reg .pred p;\nmbarrier.try_wait.parity.acquire.cluster.shared::cta.b64 p, [%1], %2;\nselp.u32 %0, 1, 0, p;\n}"
               : "=r"(ok) : "r"(bar), "r"(parity) : "memory");
  return ok != 0;
}
__device__ __forceinline__ void mbar_wait_slow(uint32_t bar, uint32_t parity) {
  uint64_t t0 = gtime();
  while (!mbar_try_cluster(bar, parity)) {
    if (gtime() - t0 > 2000000000ull) __trap();
  }
}
__device__ __forceinline__ void mbar_wait(uint32_t bar, uint32_t parity) {
  asm volatile("{\n.reg .pred p;\nFK_WAIT:\nmbarrier.try_wait.parity.shared::cta.b64 p, [%0], %1;\n@p bra FK_DONE;\nbra FK_WAIT;\nFK_DONE:\n}"
               ::"r"(bar), "r"(parity) : "memory");
}
__device__ __forceinline__ void mbar_expect_tx(uint32_t bar, uint32_t bytes) {
  asm volatile("mbarrier.arrive.expect_tx.shared::cta.b64 _, [%0], %1;" ::"r"(bar), "r"(bytes) : "memory");
}
__device__ __forceinline__ void mbar_arrive_cluster(uint32_t cluster_addr) {
  asm volatile("mbarrier.arrive.shared::cluster.b64 _, [%0];" ::"r"(cluster_addr) : "memory");
}
__device__ __forceinline__ uint32_t mapa(uint32_t addr, uint32_t rank) {
  uint32_t r;
  asm volatile("mapa.shared::cluster.u32 %0, %1, %2;" : "=r"(r) : "r"(addr), "r"(rank));
  return r;
}
__device__ __forceinline__ void tma_load(const CUtensorMap* map, int c0, int c1, uint32_t dst, uint32_t bar) {
  asm volatile("cp.async.bulk.tensor.2d.shared::cluster.global.mbarrier::complete_tx::bytes [%0], [%1, {%3, %4}], [%2];"
               ::"r"(dst), "l"(map), "r"(bar), "r"(c0), "r"(c1) : "memory");
}
__device__ __forceinline__ void tma_load_mc(const CUtensorMap* map, int c0, int c1, uint32_t dst, uint32_t bar) {
  asm volatile("cp.async.bulk.tensor.2d.shared::cluster.global.mbarrier::complete_tx::bytes.multicast::cluster [%0], [%1, {%3, %4}], [%2], %5;"
               ::"r"(dst), "l"(map), "r"(bar), "r"(c0), "r"(c1), "h"((uint16_t)3) : "memory");
}
__device__ __forceinline__ void cluster_sync() {
  asm volatile("barrier.cluster.arrive.release;\nbarrier.cluster.wait.acquire;" ::: "memory");
}
__device__ __forceinline__ void bar_sync(int id, int n) { asm volatile("bar.sync %0, %1;" ::"r"(id), "r"(n) : "memory"); }
__device__ __forceinline__ void bar_arrive(int id, int n) { asm volatile("bar.arrive %0, %1;" ::"r"(id), "r"(n) : "memory"); }

__device__ __forceinline__ void wg_fence() { asm volatile("wgmma.fence.sync.aligned;" ::: "memory"); }
__device__ __forceinline__ void wg_commit() { asm volatile("wgmma.commit_group.sync.aligned;" ::: "memory"); }
template <int N> __device__ __forceinline__ void wg_wait() { asm volatile("wgmma.wait_group.sync.aligned %0;" ::"n"(N) : "memory"); }

template <int N> __device__ __forceinline__ void pin(float (&d)[N]) {
#pragma unroll
  for (int i = 0; i < N; i++) asm volatile("" : "+f"(d[i])::"memory");
}
template <int N> __device__ __forceinline__ void pin(uint32_t (&d)[N]) {
#pragma unroll
  for (int i = 0; i < N; i++) asm volatile("" : "+r"(d[i])::"memory");
}

#define FK_ACC8(d, o) "+f"(d[o]), "+f"(d[o + 1]), "+f"(d[o + 2]), "+f"(d[o + 3]), "+f"(d[o + 4]), "+f"(d[o + 5]), "+f"(d[o + 6]), "+f"(d[o + 7])
#define FK_ACC32(d) FK_ACC8(d, 0), FK_ACC8(d, 8), FK_ACC8(d, 16), FK_ACC8(d, 24)
#define FK_ACC64(d) FK_ACC32(d), FK_ACC8(d, 32), FK_ACC8(d, 40), FK_ACC8(d, 48), FK_ACC8(d, 56)
#define FK_OUT8(d, o) "=f"(d[o]), "=f"(d[o + 1]), "=f"(d[o + 2]), "=f"(d[o + 3]), "=f"(d[o + 4]), "=f"(d[o + 5]), "=f"(d[o + 6]), "=f"(d[o + 7])
#define FK_OUT32(d) FK_OUT8(d, 0), FK_OUT8(d, 8), FK_OUT8(d, 16), FK_OUT8(d, 24)
#define FK_OUT64(d) FK_OUT32(d), FK_OUT8(d, 32), FK_OUT8(d, 40), FK_OUT8(d, 48), FK_OUT8(d, 56)
#define FK_D32 "{%0,%1,%2,%3,%4,%5,%6,%7,%8,%9,%10,%11,%12,%13,%14,%15,%16,%17,%18,%19,%20,%21,%22,%23,%24,%25,%26,%27,%28,%29,%30,%31}"
#define FK_D64 "{%0,%1,%2,%3,%4,%5,%6,%7,%8,%9,%10,%11,%12,%13,%14,%15,%16,%17,%18,%19,%20,%21,%22,%23,%24,%25,%26,%27,%28,%29,%30,%31," \
               "%32,%33,%34,%35,%36,%37,%38,%39,%40,%41,%42,%43,%44,%45,%46,%47,%48,%49,%50,%51,%52,%53,%54,%55,%56,%57,%58,%59,%60,%61,%62,%63}"

template <int TB, int ACC>
__device__ __forceinline__ void mma_n128(float (&d)[64], uint32_t a0, uint32_t a1, uint32_t a2, uint32_t a3, uint64_t db) {
  if (ACC == 2)
    asm volatile("wgmma.mma_async.sync.aligned.m64n128k16.f32.bf16.bf16 " FK_D64 ", {%64,%65,%66,%67}, %68, 0, 1, 1, %69;"
                 : FK_ACC64(d) : "r"(a0), "r"(a1), "r"(a2), "r"(a3), "l"(db), "n"(TB));
  else if (ACC == 1)
    asm volatile("wgmma.mma_async.sync.aligned.m64n128k16.f32.bf16.bf16 " FK_D64 ", {%64,%65,%66,%67}, %68, 1, 1, 1, %69;"
                 : FK_ACC64(d) : "r"(a0), "r"(a1), "r"(a2), "r"(a3), "l"(db), "n"(TB));
  else
    asm volatile("wgmma.mma_async.sync.aligned.m64n128k16.f32.bf16.bf16 " FK_D64 ", {%64,%65,%66,%67}, %68, 0, 1, 1, %69;"
                 : FK_OUT64(d) : "r"(a0), "r"(a1), "r"(a2), "r"(a3), "l"(db), "n"(TB));
}
template <int TB>
__device__ __forceinline__ void mma_n128_p(float (&d)[64], uint32_t a0, uint32_t a1, uint32_t a2, uint32_t a3, uint64_t db, int acc) {
  asm volatile("{\n.reg .pred p;\nsetp.ne.b32 p, %69, 0;\n"
               "wgmma.mma_async.sync.aligned.m64n128k16.f32.bf16.bf16 " FK_D64 ", {%64,%65,%66,%67}, %68, p, 1, 1, %70;\n}"
               : FK_ACC64(d) : "r"(a0), "r"(a1), "r"(a2), "r"(a3), "l"(db), "r"(acc), "n"(TB));
}
template <int ACC>
__device__ __forceinline__ void mma_n64(float (&d)[64], uint32_t a0, uint32_t a1, uint32_t a2, uint32_t a3, uint64_t db) {
  if (ACC)
    asm volatile("wgmma.mma_async.sync.aligned.m64n64k16.f32.bf16.bf16 " FK_D32 ", {%32,%33,%34,%35}, %36, 1, 1, 1, 1;"
                 : FK_ACC32(d) : "r"(a0), "r"(a1), "r"(a2), "r"(a3), "l"(db));
  else
    asm volatile("wgmma.mma_async.sync.aligned.m64n64k16.f32.bf16.bf16 " FK_D32 ", {%32,%33,%34,%35}, %36, 0, 1, 1, 1;"
                 : FK_ACC32(d) : "r"(a0), "r"(a1), "r"(a2), "r"(a3), "l"(db));
}

__device__ __forceinline__ float ex2(float x) { float y; asm("ex2.approx.ftz.f32 %0, %1;" : "=f"(y) : "f"(x)); return y; }
__device__ __forceinline__ float rcp(float x) { float y; asm("rcp.approx.ftz.f32 %0, %1;" : "=f"(y) : "f"(x)); return y; }
__device__ __forceinline__ float sqrt_ap(float x) { float y; asm("sqrt.approx.ftz.f32 %0, %1;" : "=f"(y) : "f"(x)); return y; }
__device__ __forceinline__ uint32_t pack2(float lo, float hi) {
  uint32_t r; asm("cvt.rn.bf16x2.f32 %0, %1, %2;" : "=r"(r) : "f"(hi), "f"(lo)); return r;
}
__device__ __forceinline__ float bf_lo(uint32_t v) { return __uint_as_float(v << 16); }
__device__ __forceinline__ float bf_hi(uint32_t v) { return __uint_as_float(v & 0xffff0000u); }
__device__ __forceinline__ float bf_round(float x) { return __bfloat162float(__float2bfloat16_rn(x)); }
__device__ __forceinline__ float quad_sum(float v) {
  v += __shfl_xor_sync(0xffffffffu, v, 1);
  v += __shfl_xor_sync(0xffffffffu, v, 2);
  return v;
}
__device__ __forceinline__ float quad_max(float v) {
  v = fmaxf(v, __shfl_xor_sync(0xffffffffu, v, 1));
  v = fmaxf(v, __shfl_xor_sync(0xffffffffu, v, 2));
  return v;
}
__device__ __forceinline__ void red4(float4* p, float a, float b, float c, float d) {
  asm volatile("red.global.v4.f32.add [%0], {%1,%2,%3,%4};" ::"l"(p), "f"(a), "f"(b), "f"(c), "f"(d) : "memory");
}
__device__ __forceinline__ unsigned int ld_acquire(const unsigned int* p) {
  unsigned int v; asm volatile("ld.acquire.gpu.global.u32 %0, [%1];" : "=r"(v) : "l"(p) : "memory"); return v;
}
__device__ __forceinline__ void wait_counter(const unsigned int* p, unsigned int target) {
  while ((int)(ld_acquire(p) - target) < 0) { }
}

constexpr uint64_t DESC_MN = (1ull << 62) | ((uint64_t)(1024 >> 4) << 32) | ((uint64_t)(8192 >> 4) << 16);
constexpr uint64_t DESC_K = (1ull << 62) | ((uint64_t)(1024 >> 4) << 32) | ((uint64_t)1 << 16);

struct Ring {
  uint32_t slot, phase;
  __device__ __forceinline__ void next() {
    if (++slot == NSLOT) { slot = 0; phase ^= 1; }
  }
};

struct Ctx {
  uint32_t ring;
  uint32_t full;
  uint32_t rel;
  bool rel_lane;
  int wg;
  Ring rd;
  __device__ __forceinline__ void wait_full() { mbar_wait(full + rd.slot * 8, rd.phase); }
  __device__ __forceinline__ uint32_t slot_lo() const { return ((ring & 0x3FFFF) >> 4) + rd.slot * (SLOT_BYTES >> 4); }
  __device__ __forceinline__ void release(uint32_t slot) {
    if (rel_lane) mbar_arrive_cluster(rel + slot * 8);
  }
  __device__ __forceinline__ void turn_wait() { bar_sync(1 + wg, 256); }
  __device__ __forceinline__ void turn_pass() { bar_arrive(2 - wg, 256); }
};

template <int NKB, int FIRST, int NA>
__device__ __forceinline__ void gemm_n128(Ctx& c, float (&acc)[64], const uint32_t (&a)[NA]) {
  c.turn_wait();
  uint32_t prev = 0;
#pragma unroll
  for (int kb = 0; kb < NKB; kb++) {
    c.wait_full();
    wg_fence();
    const uint64_t db = DESC_MN | c.slot_lo();
#pragma unroll
    for (int ks = 0; ks < 4; ks++) {
      const int i = kb * 16 + ks * 4;
      if ((kb | ks) == 0) mma_n128<1, FIRST>(acc, a[i], a[i + 1], a[i + 2], a[i + 3], db + ks * 128);
      else mma_n128<1, 1>(acc, a[i], a[i + 1], a[i + 2], a[i + 3], db + ks * 128);
    }
    wg_commit();
    if (kb == NKB - 1) c.turn_pass();
    if (kb > 0) { wg_wait<1>(); c.release(prev); }
    prev = c.rd.slot;
    c.rd.next();
  }
  wg_wait<0>();
  c.release(prev);
  pin(acc);
}
template <int NKS, int NA>
__device__ __forceinline__ void gemm_n64(Ctx& c, float (&acc)[64], const uint32_t (&a)[NA], bool pass) {
  c.turn_wait();
  uint32_t prev = 0;
  constexpr int NS = (NKS + 7) / 8;
#pragma unroll
  for (int kb = 0; kb < NS; kb++) {
    c.wait_full();
    wg_fence();
    const uint64_t db = DESC_MN | c.slot_lo();
#pragma unroll
    for (int ks = 0; ks < 8; ks++) {
      if (kb * 8 + ks < NKS) {
        const int i = (kb * 8 + ks) * 4;
        if ((kb | ks) == 0) mma_n64<0>(acc, a[i], a[i + 1], a[i + 2], a[i + 3], db + ks * 128);
        else mma_n64<1>(acc, a[i], a[i + 1], a[i + 2], a[i + 3], db + ks * 128);
      }
    }
    wg_commit();
    if (kb == NS - 1 && pass) c.turn_pass();
    if (kb > 0) { wg_wait<1>(); c.release(prev); }
    prev = c.rd.slot;
    c.rd.next();
  }
  wg_wait<0>();
  c.release(prev);
#pragma unroll
  for (int i = 0; i < 32; i++) asm volatile("" : "+f"(acc[i])::"memory");
}

template <int NG>
__device__ __forceinline__ void red_out(float4* dst, const float (&acc)[64]) {
#pragma unroll
  for (int n = 0; n < NG; n++) red4(dst + n * 128, acc[4 * n], acc[4 * n + 1], acc[4 * n + 2], acc[4 * n + 3]);
}

#define FK_STAMP(i) do { } while (0)

__global__ void __cluster_dims__(2, 1, 1) __launch_bounds__(384, 1)
fused_kernel(const __grid_constant__ CUtensorMap tm_x, const __grid_constant__ CUtensorMap tm_w1,
             const __grid_constant__ CUtensorMap tm_w3, const __grid_constant__ CUtensorMap tm_wq,
             const __grid_constant__ CUtensorMap tm_w2, const __grid_constant__ CUtensorMap tm_k,
             const __grid_constant__ CUtensorMap tm_v, const __grid_constant__ CUtensorMap tm_wo,
             const __nv_bfloat16* __restrict__ x, __nv_bfloat16* __restrict__ out) {
  extern __shared__ __align__(1024) unsigned char smem[];
  const uint32_t sbase = smem_u32(smem);
  const uint32_t bar_full = sbase + RING_BYTES;
  const uint32_t bar_empty = bar_full + NSLOT * 8;
  const uint32_t bar_done = bar_empty + NSLOT * 8;
  volatile unsigned int* s_base = reinterpret_cast<volatile unsigned int*>(smem + RING_BYTES + 2 * NSLOT * 8 + 8);

  const int tid = threadIdx.x;
  const int wg = __shfl_sync(0xffffffffu, tid >> 7, 0);
  const int cta = blockIdx.x;
  const int r = cta & 1;
  const int cl = cta >> 1;
  const int j = cl & 7;
  const int rt = (cl >> 3) * 2 + r;

  if (tid == 0) {
    mbar_init(bar_done, 8);
    for (int s = 0; s < NSLOT; s++) {
      mbar_init(bar_full + s * 8, 1);
      mbar_init(bar_empty + s * 8, 16);
    }
    asm volatile("fence.mbarrier_init.release.cluster;" ::: "memory");
    *s_base = ld_acquire(&g_cntD[rt * 32]);
  }
  __syncthreads();
  cluster_sync();

  if (wg == 2) {
    asm volatile("setmaxnreg.dec.sync.aligned.u32 24;");
    const int warp = (tid >> 5) & 3;
    if (warp == 0) {
      if ((tid & 31) == 0) {
        Ring w{0, 0};
        const uint32_t half = r * 8192;
        auto begin = [&](uint32_t bytes) {
          const uint32_t eb = bar_empty + w.slot * 8;
          if (!mbar_try_cluster(eb, w.phase ^ 1)) mbar_wait_slow(eb, w.phase ^ 1);
          mbar_expect_tx(bar_full + w.slot * 8, bytes);
        };
        auto mc = [&](const CUtensorMap* m, int col, int row) {
          begin(16384);
          tma_load_mc(m, col, row, sbase + w.slot * SLOT_BYTES + half, bar_full + w.slot * 8);
          w.next();
        };
        for (int kb = 0; kb < 9; kb++) {
          begin(16384);
          tma_load(&tm_x, kb * 64, rt * 128, sbase + w.slot * SLOT_BYTES, bar_full + w.slot * 8);
          tma_load(&tm_x, kb * 64, rt * 128 + 64, sbase + w.slot * SLOT_BYTES + 8192, bar_full + w.slot * 8);
          w.next();
        }
        const CUtensorMap* tm_up = r ? &tm_w3 : &tm_w1;
        for (int ch = 0; ch < 9; ch++)
          for (int kb = 0; kb < 9; kb++) mc(tm_up, j * 576 + ch * 64, kb * 64);
        for (int t = 0; t < 4; t++)
          for (int kb = 0; kb < 9; kb++) mc(&tm_wq, (4 * j + t) * 128 + r * 64, kb * 64);
        for (int cc = 0; cc < 4; cc++)
          for (int kb = 0; kb < 9; kb++) mc(&tm_w2, cc * 128 + r * 64, j * 576 + kb * 64);
        for (int kk = 0; kk < 4; kk++) mc(&tm_w2, 512, j * 576 + kk * 128 + r * 64);
        begin(8192);
        if (r == 0) tma_load_mc(&tm_w2, 512, j * 576 + 512, sbase + w.slot * SLOT_BYTES, bar_full + w.slot * 8);
        w.next();
        const int kvrow = 2 * j * 2048;
        for (int n = 0; n <= 64; n++) {
          if (n < 64) {
            const int row = kvrow + (n >> 5) * 2048 + (n & 15) * 128;
            mc(&tm_k, 0, row + r * 64);
            mc(&tm_k, 64, row + r * 64);
          }
          if (n > 0) {
            const int m = n - 1;
            const int row = kvrow + (m >> 5) * 2048 + (m & 15) * 128;
            mc(&tm_v, r * 64, row);
            mc(&tm_v, r * 64, row + 64);
          }
        }
        for (int cc = 0; cc < 4; cc++)
          for (int kb = 0; kb < 8; kb++) mc(&tm_wo, cc * 128 + r * 64, j * 512 + kb * 64);
        for (int kk = 0; kk < 4; kk++) mc(&tm_wo, 512, j * 512 + kk * 128 + r * 64);
      }
    } else if (warp == 1) {
      const int lane = tid & 31;
      const float4 z = make_float4(0.f, 0.f, 0.f, 0.f);
      for (int w2 = 0; w2 < 2; w2++) {
        const int o = ((rt * 2 + w2) * 72 + j * 9) * 128;
        for (int i = lane; i < 9 * 128; i += 32) { g_S[o + i] = z; g_G[o + i] = z; }
      }
      __threadfence();
      __syncwarp();
      if (lane == 0) atomicAdd(&g_cntZ[rt * 32], 1u);
    } else if (warp == 2) {
      if ((tid & 31) == 0) {
        if (sbase & 1023) __trap();
        const uint64_t t0 = gtime();
        while (!mbar_try(bar_done, 0)) {
          __nanosleep(2000);
          if (gtime() - t0 > 2000000000ull) __trap();
        }
      }
    }
    __syncwarp();
    cluster_sync();
  } else {
    asm volatile("setmaxnreg.inc.sync.aligned.u32 240;");
    const int t128 = tid & 127;
    const int lane = tid & 31;
    const int warp = t128 >> 5;
    Ctx c;
    c.ring = sbase;
    c.full = bar_full;
    c.rel = mapa(bar_empty, lane & 1);
    c.rel_lane = lane < 2;
    c.wg = wg;
    c.rd = Ring{0, 0};
    const unsigned int epoch = *s_base;
    if (wg == 1) bar_arrive(1, 256);
    FK_STAMP(0);

    float acc[64];
    uint4* const qo = g_qo + (size_t)(cta * 4 * 2 + wg) * 8 * 128 + t128;
    uint4* const hs = g_h + (size_t)(cta * 2 + wg) * 36 * 128 + t128;
    float4* const Sd = g_S + (size_t)(rt * 2 + wg) * 72 * 128 + t128;
    float4* const Gd = g_G + (size_t)(rt * 2 + wg) * 72 * 128 + t128;

    {
      uint32_t a[144];
      {
        const int row = warp * 16 + (lane & 7) + ((lane >> 3) & 1) * 8;
        const uint32_t rowoff = wg * 8192 + row * 128;
#pragma unroll
        for (int kb = 0; kb < 9; kb++) {
          c.wait_full();
          const uint32_t sb = c.ring + c.rd.slot * SLOT_BYTES + rowoff;
#pragma unroll
          for (int ks = 0; ks < 4; ks++) {
            const uint32_t addr = sb + (((2 * ks + (lane >> 4)) ^ (lane & 7)) << 4);
            const int i = kb * 16 + ks * 4;
            asm volatile("ldmatrix.sync.aligned.m8n8.x4.shared.b16 {%0,%1,%2,%3}, [%4];"
                         : "=r"(a[i]), "=r"(a[i + 1]), "=r"(a[i + 2]), "=r"(a[i + 3]) : "r"(addr) : "memory");
          }
          __syncwarp();
          c.release(c.rd.slot);
          c.rd.next();
        }
      }
      float rs0, rs1;
      {
        float s0 = 0.f, s1 = 0.f;
#pragma unroll
        for (int i = 0; i < 144; i += 2) {
          s0 += bf_lo(a[i]) + bf_hi(a[i]);
          s1 += bf_lo(a[i + 1]) + bf_hi(a[i + 1]);
        }
        const float mean0 = quad_sum(s0) * (1.f / DM), mean1 = quad_sum(s1) * (1.f / DM);
        const __nv_bfloat162 m0 = __float2bfloat162_rn(mean0), m1 = __float2bfloat162_rn(mean1);
        float q0 = 0.f, q1 = 0.f;
#pragma unroll
        for (int i = 0; i < 144; i += 2) {
          __nv_bfloat162 u = __hsub2(*reinterpret_cast<__nv_bfloat162*>(&a[i]), m0);
          __nv_bfloat162 v = __hsub2(*reinterpret_cast<__nv_bfloat162*>(&a[i + 1]), m1);
          a[i] = *reinterpret_cast<uint32_t*>(&u);
          a[i + 1] = *reinterpret_cast<uint32_t*>(&v);
          const float ul = bf_lo(a[i]), uh = bf_hi(a[i]), vl = bf_lo(a[i + 1]), vh = bf_hi(a[i + 1]);
          q0 = fmaf(ul, ul, fmaf(uh, uh, q0));
          q1 = fmaf(vl, vl, fmaf(vh, vh, q1));
        }
        const float e0 = mean0 - __low2float(m0), e1 = mean1 - __low2float(m1);
        const float var0 = fmaxf(quad_sum(q0) * (1.f / DM) - e0 * e0, 0.f);
        const float var1 = fmaxf(quad_sum(q1) * (1.f / DM) - e1 * e1, 0.f);
        rs0 = rcp(bf_round(sqrt_ap(bf_round(bf_round(var0) + 1e-5f))));
        rs1 = rcp(bf_round(sqrt_ap(bf_round(bf_round(var1) + 1e-5f))));
      }
      pin(a);
      FK_STAMP(1);
      const float LOG2E = 1.4426950408889634f;
      const float ne0 = -rs0 * LOG2E, ne1 = -rs1 * LOG2E, rr0 = rs0 * rs0, rr1 = rs1 * rs1;
#pragma unroll 1
      for (int ch = 0; ch < 13; ch++) {
        gemm_n128<9, 0>(c, acc, a);
        if (ch < 9) {
          uint32_t h[16];
#pragma unroll
          for (int i = 0; i < 16; i++) {
            const float ne = (i & 1) ? ne1 : ne0, rr = (i & 1) ? rr1 : rr0;
            const float g0 = acc[2 * i], g1 = acc[2 * i + 1];
            const float h0 = g0 * acc[32 + 2 * i] * rr * rcp(1.f + ex2(g0 * ne));
            const float h1 = g1 * acc[33 + 2 * i] * rr * rcp(1.f + ex2(g1 * ne));
            h[i] = pack2(h0, h1);
          }
#pragma unroll
          for (int i = 0; i < 4; i++) hs[(ch * 4 + i) * 128] = make_uint4(h[4 * i], h[4 * i + 1], h[4 * i + 2], h[4 * i + 3]);
        } else {
          uint4* dst = qo + (ch - 9) * 2 * 8 * 128;
#pragma unroll
          for (int i = 0; i < 8; i++) {
            dst[i * 128] = make_uint4(pack2(acc[8 * i] * rs0, acc[8 * i + 1] * rs0), pack2(acc[8 * i + 2] * rs1, acc[8 * i + 3] * rs1),
                                      pack2(acc[8 * i + 4] * rs0, acc[8 * i + 5] * rs0), pack2(acc[8 * i + 6] * rs1, acc[8 * i + 7] * rs1));
          }
        }
      }
      FK_STAMP(2);
#pragma unroll
      for (int i = 0; i < 36; i++) {
        const uint4 v = hs[i * 128];
        a[4 * i] = v.x; a[4 * i + 1] = v.y; a[4 * i + 2] = v.z; a[4 * i + 3] = v.w;
      }
      wait_counter(&g_cntZ[rt * 32], epoch + 8);
      pin(a);
#pragma unroll 1
      for (int cc = 0; cc < 4; cc++) {
        gemm_n128<9, 0>(c, acc, a);
        red_out<16>(Gd + cc * 16 * 128, acc);
      }
      gemm_n64<36>(c, acc, a, true);
      red_out<8>(Gd + 64 * 128, acc);
      FK_STAMP(3);
    }

    uint32_t ao[128];
    float o[64];
    {
      const float SC = 0.08838834764831845f * 1.4426950408889634f;
      uint32_t q[32], p[32];
      float m0, m1, l0, l1;
#pragma unroll
      for (int i = 0; i < 8; i++) {
        const uint4 v = qo[i * 128];
        q[4 * i] = v.x; q[4 * i + 1] = v.y; q[4 * i + 2] = v.z; q[4 * i + 3] = v.w;
      }
      pin(q);
      auto issue_qk = [&](uint32_t& s0, uint32_t& s1) {
#pragma unroll
        for (int h = 0; h < 2; h++) {
          c.wait_full();
          wg_fence();
          const uint64_t db = DESC_K | c.slot_lo();
#pragma unroll
          for (int ks = 0; ks < 4; ks++) {
            const int i = h * 16 + ks * 4;
            if ((h | ks) == 0) mma_n128<0, 0>(acc, q[i], q[i + 1], q[i + 2], q[i + 3], db + ks * 2);
            else mma_n128<0, 1>(acc, q[i], q[i + 1], q[i + 2], q[i + 3], db + ks * 2);
          }
          if (h == 0) s0 = c.rd.slot; else s1 = c.rd.slot;
          c.rd.next();
        }
        wg_commit();
      };
      auto issue_pv = [&](uint32_t& s0, uint32_t& s1, int accumulate) {
#pragma unroll
        for (int h = 0; h < 2; h++) {
          c.wait_full();
          wg_fence();
          const uint64_t db = DESC_MN | c.slot_lo();
#pragma unroll
          for (int ks = 0; ks < 4; ks++) {
            const int i = h * 16 + ks * 4;
            if ((h | ks) == 0) mma_n128_p<1>(o, p[i], p[i + 1], p[i + 2], p[i + 3], db + ks * 128, accumulate);
            else mma_n128<1, 1>(o, p[i], p[i + 1], p[i + 2], p[i + 3], db + ks * 128);
          }
          if (h == 0) s0 = c.rd.slot; else s1 = c.rd.slot;
          c.rd.next();
        }
        wg_commit();
      };
      auto softmax = [&](bool fresh, float& f0, float& f1) {
        float x0 = fmaxf(acc[0], acc[1]), x1 = fmaxf(acc[2], acc[3]);
#pragma unroll
        for (int n = 1; n < 16; n++) {
          x0 = fmaxf(x0, fmaxf(acc[4 * n], acc[4 * n + 1]));
          x1 = fmaxf(x1, fmaxf(acc[4 * n + 2], acc[4 * n + 3]));
        }
        x0 = quad_max(x0);
        x1 = quad_max(x1);
        const float p0 = fresh ? -INFINITY : m0, p1 = fresh ? -INFINITY : m1;
        m0 = fmaxf(p0, x0);
        m1 = fmaxf(p1, x1);
        f0 = ex2((p0 - m0) * SC);
        f1 = ex2((p1 - m1) * SC);
        const float b0 = -m0 * SC, b1 = -m1 * SC;
        float s0 = 0.f, s1 = 0.f;
#pragma unroll
        for (int n = 0; n < 16; n++) {
          acc[4 * n] = ex2(fmaf(acc[4 * n], SC, b0));
          acc[4 * n + 1] = ex2(fmaf(acc[4 * n + 1], SC, b0));
          acc[4 * n + 2] = ex2(fmaf(acc[4 * n + 2], SC, b1));
          acc[4 * n + 3] = ex2(fmaf(acc[4 * n + 3], SC, b1));
          s0 += acc[4 * n] + acc[4 * n + 1];
          s1 += acc[4 * n + 2] + acc[4 * n + 3];
        }
        l0 = fmaf(l0, f0, s0);
        l1 = fmaf(l1, f1, s1);
      };
      auto pack_p = [&]() {
#pragma unroll
        for (int i = 0; i < 32; i++) p[i] = pack2(acc[2 * i], acc[2 * i + 1]);
      };

      uint32_t k0, k1, v0, v1;
      float f0, f1;
      l0 = 0.f; l1 = 0.f; m0 = 0.f; m1 = 0.f;
      c.turn_wait();
      issue_qk(k0, k1);
      c.turn_pass();
      wg_wait<0>();
      pin(acc);
      c.release(k0); c.release(k1);
      softmax(true, f0, f1);
      pack_p();
#pragma unroll
      for (int i = 0; i < 64; i++) o[i] = 0.f;
#pragma unroll 1
      for (int n = 0; n < 63; n++) {
        const bool boundary = (n & 15) == 15;
        pin(p); pin(o); pin(q);
        c.turn_wait();
        issue_qk(k0, k1);
        issue_pv(v0, v1, (n & 15) != 0);
        c.turn_pass();
        wg_wait<1>();
        pin(acc);
        c.release(k0); c.release(k1);
        if ((n & 15) == 14 && n < 48) {
          const uint4* src = qo + ((n >> 4) + 1) * 2 * 8 * 128;
#pragma unroll
          for (int i = 0; i < 8; i++) {
            const uint4 v = src[i * 128];
            q[4 * i] = v.x; q[4 * i + 1] = v.y; q[4 * i + 2] = v.z; q[4 * i + 3] = v.w;
          }
        }
        const float lo0 = l0, lo1 = l1;
        softmax(boundary, f0, f1);
        if (boundary) {
          f0 = rcp(quad_sum(lo0));
          f1 = rcp(quad_sum(lo1));
        }
        wg_wait<0>();
        pin(o); pin(acc);
        c.release(v0); c.release(v1);
#pragma unroll
        for (int i = 0; i < 16; i++) {
          o[4 * i] *= f0; o[4 * i + 1] *= f0; o[4 * i + 2] *= f1; o[4 * i + 3] *= f1;
        }
        if (boundary) {
          uint4* dst = qo + (n >> 4) * 2 * 8 * 128;
#pragma unroll
          for (int i = 0; i < 8; i++)
            dst[i * 128] = make_uint4(pack2(o[8 * i], o[8 * i + 1]), pack2(o[8 * i + 2], o[8 * i + 3]),
                                      pack2(o[8 * i + 4], o[8 * i + 5]), pack2(o[8 * i + 6], o[8 * i + 7]));
        }
        pack_p();
      }
      pin(p); pin(o);
      c.turn_wait();
      issue_pv(v0, v1, 1);
      c.turn_pass();
#pragma unroll
      for (int i = 0; i < 24; i++) {
        const uint4 v = qo[(i >> 3) * 2 * 8 * 128 + (i & 7) * 128];
        ao[4 * i] = v.x; ao[4 * i + 1] = v.y; ao[4 * i + 2] = v.z; ao[4 * i + 3] = v.w;
      }
      f0 = rcp(quad_sum(l0));
      f1 = rcp(quad_sum(l1));
      wg_wait<0>();
      pin(o);
      c.release(v0); c.release(v1);
#pragma unroll
      for (int i = 0; i < 16; i++) {
        ao[96 + 2 * i] = pack2(o[4 * i] * f0, o[4 * i + 1] * f0);
        ao[97 + 2 * i] = pack2(o[4 * i + 2] * f1, o[4 * i + 3] * f1);
      }
      FK_STAMP(4);
    }
    pin(ao);
#pragma unroll 1
    for (int cc = 0; cc < 4; cc++) {
      gemm_n128<8, 2>(c, o, ao);
      red_out<16>(Sd + cc * 16 * 128, o);
    }
    gemm_n64<32>(c, o, ao, wg == 0);
    red_out<8>(Sd + 64 * 128, o);
    FK_STAMP(5);
    __threadfence();
    bar_sync(3, 256);
    if (tid == 0) atomicAdd(&g_cntD[rt * 32], 1u);
    {
      const int row = rt * 128 + wg * 64 + warp * 16 + (lane >> 2);
      const int col = j * 72 + (lane & 3) * 2;
      const uint32_t* xp = reinterpret_cast<const uint32_t*>(x + (size_t)row * DM + col);
      uint32_t* op = reinterpret_cast<uint32_t*>(out + (size_t)row * DM + col);
      uint32_t xa[9], xb[9];
#pragma unroll
      for (int i = 0; i < 9; i++) { xa[i] = __ldg(xp + i * 4); xb[i] = __ldg(xp + i * 4 + 8 * DM / 2); }
      wait_counter(&g_cntD[rt * 32], epoch + 8);
      FK_STAMP(6);
      float4 sv[9], gv[9];
#pragma unroll
      for (int i = 0; i < 9; i++) { sv[i] = __ldcg(Sd + (j * 9 + i) * 128); gv[i] = __ldcg(Gd + (j * 9 + i) * 128); }
      auto fin = [&](float xv, float s, float g) {
        const float gb = bf_round(g);
        const float sg = bf_round(gb * rcp(1.f + ex2(-gb * 1.4426950408889634f)));
        return xv + bf_round(bf_round(s) * sg);
      };
#pragma unroll
      for (int i = 0; i < 9; i++) {
        op[i * 4] = pack2(fin(bf_lo(xa[i]), sv[i].x, gv[i].x), fin(bf_hi(xa[i]), sv[i].y, gv[i].y));
        op[i * 4 + 8 * DM / 2] = pack2(fin(bf_lo(xb[i]), sv[i].z, gv[i].z), fin(bf_hi(xb[i]), sv[i].w, gv[i].w));
      }
    }
    FK_STAMP(7);
    if (lane == 0) asm volatile("mbarrier.arrive.shared::cta.b64 _, [%0];" ::"r"(bar_done) : "memory");
    cluster_sync();
  }
}

typedef CUresult (*EncodeFn)(CUtensorMap*, CUtensorMapDataType, cuuint32_t, void*, const cuuint64_t*, const cuuint64_t*,
                             const cuuint32_t*, const cuuint32_t*, CUtensorMapInterleave, CUtensorMapSwizzle,
                             CUtensorMapL2promotion, CUtensorMapFloatOOBfill);

static void make_map(EncodeFn enc, CUtensorMap* m, const void* ptr, uint64_t rows, uint64_t cols) {
  cuuint64_t dims[2] = {cols, rows};
  cuuint64_t strides[1] = {cols * 2};
  cuuint32_t box[2] = {64, 64};
  cuuint32_t es[2] = {1, 1};
  enc(m, CU_TENSOR_MAP_DATA_TYPE_BFLOAT16, 2, const_cast<void*>(ptr), dims, strides, box, es, CU_TENSOR_MAP_INTERLEAVE_NONE,
      CU_TENSOR_MAP_SWIZZLE_128B, CU_TENSOR_MAP_L2_PROMOTION_L2_128B, CU_TENSOR_MAP_FLOAT_OOB_FILL_NONE);
}

}

extern "C" void kernel_launch(void* const* d_in, const int* in_sizes, int n_in, void* d_out, int out_size) {
  using namespace fk;
  (void)in_sizes; (void)n_in; (void)out_size;
  static EncodeFn enc = nullptr;
  if (!enc) {
    void* fn = nullptr;
    cudaDriverEntryPointQueryResult st;
    cudaGetDriverEntryPoint("cuTensorMapEncodeTiled", &fn, cudaEnableDefault, &st);
    enc = (EncodeFn)fn;
    cudaFuncSetAttribute(fused_kernel, cudaFuncAttributeMaxDynamicSharedMemorySize, SMEM_BYTES);
  }
  CUtensorMap mx, mw1, mw3, mwq, mw2, mk, mv, mwo;
  make_map(enc, &mx, d_in[0], SEQ, DM);
  make_map(enc, &mk, d_in[1], 16 * SEQ, 128);
  make_map(enc, &mv, d_in[2], 16 * SEQ, 128);
  make_map(enc, &mwq, d_in[3], DM, 4096);
  make_map(enc, &mwo, d_in[4], 4096, DM);
  make_map(enc, &mw1, d_in[6], DM, FF);
  make_map(enc, &mw3, d_in[7], DM, FF);
  make_map(enc, &mw2, d_in[8], FF, DM);
  fused_kernel<<<NCTA, 384, SMEM_BYTES>>>(mx, mw1, mw3, mwq, mw2, mk, mv, mwo, (const __nv_bfloat16*)d_in[0],
                                          (__nv_bfloat16*)d_out);
}
```

```cpp
#include <cuda_runtime.h>
#include <cuda_bf16.h>
#include <cuda.h>
#include <stdint.h>

namespace fk {

constexpr int SEQ = 2048, DM = 576, FF = 4608;
constexpr int NSLOT = 14;
constexpr int SLOT_BYTES = 16384;
constexpr int RING_BYTES = NSLOT * SLOT_BYTES;
constexpr int SMEM_BYTES = RING_BYTES + 512 + 2048;
constexpr int NCTA = 128;
constexpr int NPAIR = NSLOT / 2;
constexpr int SPLIT = 7;

__device__ uint4 g_qo[NCTA * 4 * 2 * 8 * 128];
__device__ uint4 g_h[NCTA * 2 * 36 * 128];
__device__ uint4 g_S[16 * 2 * 36 * 128];
__device__ uint4 g_G[16 * 2 * 36 * 128];
__device__ unsigned int g_cntZ[16 * 32];
__device__ unsigned int g_cntD[16 * 32];
__device__ unsigned int g_cntQ[16 * 32];
__device__ unsigned int g_cntY[16 * 32];

__device__ __forceinline__ uint32_t smem_u32(const void* p) { return (uint32_t)__cvta_generic_to_shared(p); }
__device__ __forceinline__ uint64_t gtime() { uint64_t t; asm volatile("mov.u64 %0, %globaltimer;" : "=l"(t)); return t; }

__device__ __forceinline__ void mbar_init(uint32_t bar, uint32_t cnt) {
  asm volatile("mbarrier.init.shared::cta.b64 [%0], %1;" ::"r"(bar), "r"(cnt) : "memory");
}
__device__ __forceinline__ bool mbar_try_long(uint32_t bar, uint32_t parity) {
  uint32_t ok;
  asm volatile("{\n.reg .pred p;\nmbarrier.try_wait.parity.shared::cta.b64 p, [%1], %2, 50000;\nselp.u32 %0, 1, 0, p;\n}"
               : "=r"(ok) : "r"(bar), "r"(parity) : "memory");
  return ok != 0;
}
__device__ __forceinline__ void mbar_wait(uint32_t bar, uint32_t parity) {
  asm volatile("{\n.reg .pred p;\nFK_WAIT:\nmbarrier.try_wait.parity.shared::cta.b64 p, [%0], %1;\n@p bra FK_DONE;\nbra FK_WAIT;\nFK_DONE:\n}"
               ::"r"(bar), "r"(parity) : "memory");
}
__device__ __forceinline__ uint32_t mbar_test(uint32_t bar, uint32_t parity) {
  uint32_t ok;
  asm volatile("{\n.reg .pred p;\nmbarrier.test_wait.parity.shared::cta.b64 p, [%1], %2;\nselp.u32 %0, 1, 0, p;\n}"
               : "=r"(ok) : "r"(bar), "r"(parity) : "memory");
  return ok;
}
__device__ __forceinline__ uint32_t mbar_test2(uint32_t b0, uint32_t p0, uint32_t b1, uint32_t p1) {
  uint32_t ok;
  asm volatile("{\n.reg .pred a, b;\n"
               "mbarrier.test_wait.parity.shared::cta.b64 a, [%1], %2;\n"
               "mbarrier.test_wait.parity.shared::cta.b64 b, [%3], %4;\n"
               "and.pred a, a, b;\nselp.u32 %0, 1, 0, a;\n}"
               : "=r"(ok) : "r"(b0), "r"(p0), "r"(b1), "r"(p1) : "memory");
  return ok;
}
__device__ __forceinline__ void mbar_arrive(uint32_t bar) {
  asm volatile("mbarrier.arrive.shared::cta.b64 _, [%0];" ::"r"(bar) : "memory");
}
__device__ __forceinline__ void l2_prefetch(const void* p, uint32_t bytes) {
  asm volatile("cp.async.bulk.prefetch.L2.global [%0], %1;" ::"l"(p), "r"(bytes) : "memory");
}
__device__ __forceinline__ int fresh_tid() {
  int t; asm volatile("mov.u32 %0, %tid.x;" : "=r"(t)); return t;
}
__device__ __forceinline__ void mbar_expect_tx(uint32_t bar, uint32_t bytes) {
  asm volatile("mbarrier.arrive.expect_tx.shared::cta.b64 _, [%0], %1;" ::"r"(bar), "r"(bytes) : "memory");
}
__device__ __forceinline__ void mbar_arrive_cluster(uint32_t cluster_addr) {
  asm volatile("mbarrier.arrive.shared::cluster.b64 _, [%0];" ::"r"(cluster_addr) : "memory");
}
__device__ __forceinline__ uint32_t mapa(uint32_t addr, uint32_t rank) {
  uint32_t r;
  asm volatile("mapa.shared::cluster.u32 %0, %1, %2;" : "=r"(r) : "r"(addr), "r"(rank));
  return r;
}
__device__ __forceinline__ void tma_load(const CUtensorMap* map, int c0, int c1, uint32_t dst, uint32_t bar) {
  asm volatile("cp.async.bulk.tensor.2d.shared::cluster.global.mbarrier::complete_tx::bytes [%0], [%1, {%3, %4}], [%2];"
               ::"r"(dst), "l"(map), "r"(bar), "r"(c0), "r"(c1) : "memory");
}
__device__ __forceinline__ void tma_load_mc(const CUtensorMap* map, int c0, int c1, uint32_t dst, uint32_t bar) {
  asm volatile("cp.async.bulk.tensor.2d.shared::cluster.global.mbarrier::complete_tx::bytes.multicast::cluster [%0], [%1, {%3, %4}], [%2], %5;"
               ::"r"(dst), "l"(map), "r"(bar), "r"(c0), "r"(c1), "h"((uint16_t)3) : "memory");
}
__device__ __forceinline__ void tma_load_mc_hint(const CUtensorMap* map, int c0, int c1, uint32_t dst, uint32_t bar, uint64_t pol) {
  asm volatile("cp.async.bulk.tensor.2d.shared::cluster.global.mbarrier::complete_tx::bytes.multicast::cluster.L2::cache_hint [%0], [%1, {%3, %4}], [%2], %5, %6;"
               ::"r"(dst), "l"(map), "r"(bar), "r"(c0), "r"(c1), "h"((uint16_t)3), "l"(pol) : "memory");
}
__device__ __forceinline__ void bulk_load(uint32_t dst, const void* src, uint32_t bytes, uint32_t bar) {
  asm volatile("cp.async.bulk.shared::cluster.global.mbarrier::complete_tx::bytes [%0], [%1], %2, [%3];"
               ::"r"(dst), "l"(src), "r"(bytes), "r"(bar) : "memory");
}
__device__ __forceinline__ void cluster_arrive() { asm volatile("barrier.cluster.arrive.relaxed.aligned;" ::: "memory"); }
__device__ __forceinline__ void cluster_wait() { asm volatile("barrier.cluster.wait.aligned;" ::: "memory"); }
__device__ __forceinline__ void bar_sync(int id, int n) { asm volatile("bar.sync %0, %1;" ::"r"(id), "r"(n) : "memory"); }
__device__ __forceinline__ void bar_arrive(int id, int n) { asm volatile("bar.arrive %0, %1;" ::"r"(id), "r"(n) : "memory"); }

__device__ __forceinline__ void wg_fence() { asm volatile("wgmma.fence.sync.aligned;" ::: "memory"); }
__device__ __forceinline__ void wg_commit() { asm volatile("wgmma.commit_group.sync.aligned;" ::: "memory"); }
template <int N> __device__ __forceinline__ void wg_wait() { asm volatile("wgmma.wait_group.sync.aligned %0;" ::"n"(N) : "memory"); }

template <int N> __device__ __forceinline__ void pin(float (&d)[N]) {
#pragma unroll
  for (int i = 0; i < N; i++) asm volatile("" : "+f"(d[i])::"memory");
}
template <int N> __device__ __forceinline__ void pin(uint32_t (&d)[N]) {
#pragma unroll
  for (int i = 0; i < N; i++) asm volatile("" : "+r"(d[i])::"memory");
}

#define FK_ACC8(d, o) "+f"(d[o]), "+f"(d[o + 1]), "+f"(d[o + 2]), "+f"(d[o + 3]), "+f"(d[o + 4]), "+f"(d[o + 5]), "+f"(d[o + 6]), "+f"(d[o + 7])
#define FK_ACC32(d) FK_ACC8(d, 0), FK_ACC8(d, 8), FK_ACC8(d, 16), FK_ACC8(d, 24)
#define FK_ACC64(d) FK_ACC32(d), FK_ACC8(d, 32), FK_ACC8(d, 40), FK_ACC8(d, 48), FK_ACC8(d, 56)
#define FK_OUT8(d, o) "=f"(d[o]), "=f"(d[o + 1]), "=f"(d[o + 2]), "=f"(d[o + 3]), "=f"(d[o + 4]), "=f"(d[o + 5]), "=f"(d[o + 6]), "=f"(d[o + 7])
#define FK_OUT32(d) FK_OUT8(d, 0), FK_OUT8(d, 8), FK_OUT8(d, 16), FK_OUT8(d, 24)
#define FK_OUT64(d) FK_OUT32(d), FK_OUT8(d, 32), FK_OUT8(d, 40), FK_OUT8(d, 48), FK_OUT8(d, 56)
#define FK_D32 "{%0,%1,%2,%3,%4,%5,%6,%7,%8,%9,%10,%11,%12,%13,%14,%15,%16,%17,%18,%19,%20,%21,%22,%23,%24,%25,%26,%27,%28,%29,%30,%31}"
#define FK_D64 "{%0,%1,%2,%3,%4,%5,%6,%7,%8,%9,%10,%11,%12,%13,%14,%15,%16,%17,%18,%19,%20,%21,%22,%23,%24,%25,%26,%27,%28,%29,%30,%31," \
               "%32,%33,%34,%35,%36,%37,%38,%39,%40,%41,%42,%43,%44,%45,%46,%47,%48,%49,%50,%51,%52,%53,%54,%55,%56,%57,%58,%59,%60,%61,%62,%63}"

template <int TB, int ACC>
__device__ __forceinline__ void mma_n128(float (&d)[64], uint32_t a0, uint32_t a1, uint32_t a2, uint32_t a3, uint64_t db) {
  if (ACC == 2)
    asm volatile("wgmma.mma_async.sync.aligned.m64n128k16.f32.bf16.bf16 " FK_D64 ", {%64,%65,%66,%67}, %68, 0, 1, 1, %69;"
                 : FK_ACC64(d) : "r"(a0), "r"(a1), "r"(a2), "r"(a3), "l"(db), "n"(TB));
  else if (ACC == 1)
    asm volatile("wgmma.mma_async.sync.aligned.m64n128k16.f32.bf16.bf16 " FK_D64 ", {%64,%65,%66,%67}, %68, 1, 1, 1, %69;"
                 : FK_ACC64(d) : "r"(a0), "r"(a1), "r"(a2), "r"(a3), "l"(db), "n"(TB));
  else
    asm volatile("wgmma.mma_async.sync.aligned.m64n128k16.f32.bf16.bf16 " FK_D64 ", {%64,%65,%66,%67}, %68, 0, 1, 1, %69;"
                 : FK_OUT64(d) : "r"(a0), "r"(a1), "r"(a2), "r"(a3), "l"(db), "n"(TB));
}
template <int TB>
__device__ __forceinline__ void mma_n128_p(float (&d)[64], uint32_t a0, uint32_t a1, uint32_t a2, uint32_t a3, uint64_t db, int acc) {
  asm volatile("{\n.reg .pred p;\nsetp.ne.b32 p, %69, 0;\n"
               "wgmma.mma_async.sync.aligned.m64n128k16.f32.bf16.bf16 " FK_D64 ", {%64,%65,%66,%67}, %68, p, 1, 1, %70;\n}"
               : FK_ACC64(d) : "r"(a0), "r"(a1), "r"(a2), "r"(a3), "l"(db), "r"(acc), "n"(TB));
}
template <int ACC>
__device__ __forceinline__ void mma_n64(float (&d)[64], uint32_t a0, uint32_t a1, uint32_t a2, uint32_t a3, uint64_t db) {
  if (ACC == 3)
    asm volatile("wgmma.mma_async.sync.aligned.m64n64k16.f32.bf16.bf16 " FK_D32 ", {%32,%33,%34,%35}, %36, 0, 1, 1, 1;"
                 : FK_OUT32(d) : "r"(a0), "r"(a1), "r"(a2), "r"(a3), "l"(db));
  else if (ACC)
    asm volatile("wgmma.mma_async.sync.aligned.m64n64k16.f32.bf16.bf16 " FK_D32 ", {%32,%33,%34,%35}, %36, 1, 1, 1, 1;"
                 : FK_ACC32(d) : "r"(a0), "r"(a1), "r"(a2), "r"(a3), "l"(db));
  else
    asm volatile("wgmma.mma_async.sync.aligned.m64n64k16.f32.bf16.bf16 " FK_D32 ", {%32,%33,%34,%35}, %36, 0, 1, 1, 1;"
                 : FK_ACC32(d) : "r"(a0), "r"(a1), "r"(a2), "r"(a3), "l"(db));
}

__device__ __forceinline__ void mma16816(float& d0, float& d1, float& d2, float& d3, uint32_t a0, uint32_t a1, uint32_t a2, uint32_t a3,
                                         uint32_t b0, uint32_t b1) {
  asm volatile("mma.sync.aligned.m16n8k16.row.col.f32.bf16.bf16.f32 {%0,%1,%2,%3}, {%4,%5,%6,%7}, {%8,%9}, {%0,%1,%2,%3};"
               : "+f"(d0), "+f"(d1), "+f"(d2), "+f"(d3) : "r"(a0), "r"(a1), "r"(a2), "r"(a3), "r"(b0), "r"(b1));
}
__device__ __forceinline__ float ex2(float x) { float y; asm("ex2.approx.ftz.f32 %0, %1;" : "=f"(y) : "f"(x)); return y; }
__device__ __forceinline__ float rcp(float x) { float y; asm("rcp.approx.ftz.f32 %0, %1;" : "=f"(y) : "f"(x)); return y; }
__device__ __forceinline__ float sqrt_ap(float x) { float y; asm("sqrt.approx.ftz.f32 %0, %1;" : "=f"(y) : "f"(x)); return y; }
__device__ __forceinline__ uint32_t pack2(float lo, float hi) {
  uint32_t r; asm("cvt.rn.bf16x2.f32 %0, %1, %2;" : "=r"(r) : "f"(hi), "f"(lo)); return r;
}
__device__ __forceinline__ float bf_lo(uint32_t v) { return __uint_as_float(v << 16); }
__device__ __forceinline__ float bf_hi(uint32_t v) { return __uint_as_float(v & 0xffff0000u); }
__device__ __forceinline__ float bf_round(float x) { return __bfloat162float(__float2bfloat16_rn(x)); }
__device__ __forceinline__ float quad_sum(float v) {
  v += __shfl_xor_sync(0xffffffffu, v, 1);
  v += __shfl_xor_sync(0xffffffffu, v, 2);
  return v;
}
__device__ __forceinline__ float quad_max(float v) {
  v = fmaxf(v, __shfl_xor_sync(0xffffffffu, v, 1));
  v = fmaxf(v, __shfl_xor_sync(0xffffffffu, v, 2));
  return v;
}
__device__ __forceinline__ void red8(uint4* p, const float* v) {
  asm volatile("red.global.add.noftz.v4.bf16x2 [%0], {%1,%2,%3,%4};"
               ::"l"(p), "r"(pack2(v[0], v[1])), "r"(pack2(v[2], v[3])), "r"(pack2(v[4], v[5])), "r"(pack2(v[6], v[7])) : "memory");
}
__device__ __forceinline__ unsigned int ld_acquire(const unsigned int* p) {
  unsigned int v; asm volatile("ld.acquire.gpu.global.u32 %0, [%1];" : "=r"(v) : "l"(p) : "memory"); return v;
}

constexpr uint64_t DESC_MN = (1ull << 62) | ((uint64_t)(1024 >> 4) << 32) | ((uint64_t)(8192 >> 4) << 16);
constexpr uint64_t DESC_K = (1ull << 62) | ((uint64_t)(1024 >> 4) << 32) | ((uint64_t)1 << 16);

template <int N>
struct RingT {
  uint32_t slot, phase;
  __device__ __forceinline__ void next() {
    if (++slot == N) { slot = 0; phase ^= 1; }
  }
};
typedef RingT<NSLOT> Ring;
typedef RingT<NPAIR> Ring2;

constexpr uint32_t B_FULL = 0, B_EMPTY = NSLOT * 8, B_FULL2 = 2 * NSLOT * 8, B_EMPTY2 = B_FULL2 + NPAIR * 8,
                   B_DONE = B_EMPTY2 + NPAIR * 8, B_ZERO = B_DONE + 8, B_RED = B_ZERO + 8, B_STG = B_RED + 8, B_MARK = B_STG + 16, B_ZBUF = 512;

struct Ctx {
  uint32_t ring;
  uint32_t bars;
  uint32_t rel;
  bool rel_lane;
  int wg;
  Ring rd;
  Ring2 rp;
  __device__ __forceinline__ uint32_t ring_lo() const { return (ring & 0x3FFFF) >> 4; }
  __device__ __forceinline__ void wait_full() { mbar_wait(bars + B_FULL + rd.slot * 8, rd.phase); }
  __device__ __forceinline__ uint32_t slot_lo() const { return ring_lo() + rd.slot * (SLOT_BYTES >> 4); }
  __device__ __forceinline__ void release(uint32_t slot) {
    if (rel_lane) mbar_arrive_cluster(rel + B_EMPTY + slot * 8);
  }
  __device__ __forceinline__ void wait_full2() { mbar_wait(bars + B_FULL2 + rp.slot * 8, rp.phase); }
  __device__ __forceinline__ void release2(uint32_t pair) {
    if (rel_lane) mbar_arrive_cluster(rel + B_EMPTY2 + pair * 8);
  }
  __device__ __forceinline__ void turn_wait() { bar_sync(1 + wg, 256); }
  __device__ __forceinline__ void turn_pass() { bar_arrive(2 - wg, 256); }
};

__device__ __forceinline__ void gemm_n128(Ctx& c, float (&acc)[64], uint32_t (&a)[144], const uint4* next, int reload) {
  c.wait_full();
  c.turn_wait();
  uint32_t p1 = 0, p2 = 0, ok = 1;
  auto refill = [&](int kb) {
    if (kb < reload) {
#pragma unroll
      for (int i = 0; i < 4; i++) {
        const uint4 v = __ldcs(next + (kb * 4 + i) * 128);
        const int e = kb * 16 + i * 4;
        a[e] = v.x; a[e + 1] = v.y; a[e + 2] = v.z; a[e + 3] = v.w;
      }
    }
  };
#pragma unroll
  for (int kb = 0; kb < 9; kb++) {
    if (!ok) c.wait_full();
    wg_fence();
    const uint64_t db = DESC_MN | c.slot_lo();
#pragma unroll
    for (int ks = 0; ks < 4; ks++) {
      const int i = kb * 16 + ks * 4;
      if ((kb | ks) == 0) mma_n128<1, 0>(acc, a[i], a[i + 1], a[i + 2], a[i + 3], db + ks * 128);
      else mma_n128<1, 1>(acc, a[i], a[i + 1], a[i + 2], a[i + 3], db + ks * 128);
    }
    wg_commit();
    const uint32_t cur = c.rd.slot;
    c.rd.next();
    if (kb == 8) c.turn_pass();
    else ok = mbar_test(c.bars + B_FULL + c.rd.slot * 8, c.rd.phase);
    if (kb >= 2) {
      wg_wait<2>();
      c.release(p2);
    }
    if (kb == 5) refill(0);
    if (kb == 6) refill(1);
    if (kb == 7) refill(2);
    p2 = p1;
    p1 = cur;
  }
  refill(3);
  refill(4);
  wg_wait<1>();
  c.release(p2);
  refill(5);
  refill(6);
  wg_wait<0>();
  c.release(p1);
  refill(7);
  pin(acc);
}
__device__ __forceinline__ void gemm_n64(Ctx& c, float (&acc)[64], const uint32_t (&a)[144]) {
  c.wait_full();
  c.turn_wait();
  uint32_t p1 = 0, p2 = 0, ok = 1;
#pragma unroll
  for (int kb = 0; kb < 5; kb++) {
    if (!ok) c.wait_full();
    wg_fence();
    const uint64_t db = DESC_MN | c.slot_lo();
#pragma unroll
    for (int ks = 0; ks < 8; ks++) {
      if (kb * 8 + ks < 36) {
        const int i = (kb * 8 + ks) * 4;
        if ((kb | ks) == 0) mma_n64<3>(acc, a[i], a[i + 1], a[i + 2], a[i + 3], db + ks * 128);
        else mma_n64<1>(acc, a[i], a[i + 1], a[i + 2], a[i + 3], db + ks * 128);
      }
    }
    wg_commit();
    const uint32_t cur = c.rd.slot;
    c.rd.next();
    if (kb == 4) c.turn_pass();
    else ok = mbar_test(c.bars + B_FULL + c.rd.slot * 8, c.rd.phase);
    if (kb >= 2) { wg_wait<2>(); c.release(p2); }
    p2 = p1;
    p1 = cur;
  }
  wg_wait<1>();
  c.release(p2);
  wg_wait<0>();
  c.release(p1);
#pragma unroll
  for (int i = 0; i < 32; i++) asm volatile("" : "+f"(acc[i])::"memory");
}
__device__ __forceinline__ void gemm_s(Ctx& c, float (&acc)[64], const uint32_t (&a)[128], int nrel) {
  c.wait_full2();
  c.turn_wait();
  uint32_t prev = 0, ok = 1;
#pragma unroll
  for (int st = 0; st < 4; st++) {
    if (!ok) c.wait_full2();
    wg_fence();
    const uint64_t db = DESC_MN | (c.ring_lo() + c.rp.slot * (2 * SLOT_BYTES >> 4));
#pragma unroll
    for (int ks = 0; ks < 8; ks++) {
      const int i = (st * 8 + ks) * 4;
      const uint64_t d = db + (ks >> 2) * (SLOT_BYTES >> 4) + (ks & 3) * 128;
      if ((st | ks) == 0) mma_n128<1, 2>(acc, a[i], a[i + 1], a[i + 2], a[i + 3], d);
      else mma_n128<1, 1>(acc, a[i], a[i + 1], a[i + 2], a[i + 3], d);
    }
    wg_commit();
    const uint32_t cur = c.rp.slot;
    c.rp.next();
    if (st == 3) c.turn_pass();
    else ok = mbar_test(c.bars + B_FULL2 + c.rp.slot * 8, c.rp.phase);
    if (st > 0) { wg_wait<1>(); if (st <= nrel) c.release2(prev); }
    prev = cur;
  }
  wg_wait<0>();
  if (nrel == 4) c.release2(prev);
  pin(acc);
}
__device__ __forceinline__ int s_slice(int j, int i) { return i == 0 ? 8 : ((j + i) & 7); }

template <int NG>
__device__ __forceinline__ void red_out(uint4* dst, const float (&acc)[64]) {
#pragma unroll
  for (int n = 0; n < NG / 2; n++) red8(dst + n * 128, &acc[8 * n]);
}

template <bool OFF>
__global__ void __cluster_dims__(2, 1, 1) __launch_bounds__(384, 1)
fused_kernel(const __grid_constant__ CUtensorMap tm_x, const __grid_constant__ CUtensorMap tm_w1,
             const __grid_constant__ CUtensorMap tm_w3, const __grid_constant__ CUtensorMap tm_wq,
             const __grid_constant__ CUtensorMap tm_w2, const __grid_constant__ CUtensorMap tm_k,
             const __grid_constant__ CUtensorMap tm_v, const __grid_constant__ CUtensorMap tm_wo,
             const __nv_bfloat16* __restrict__ x, __nv_bfloat16* __restrict__ out, const char* __restrict__ wog) {
  extern __shared__ __align__(1024) unsigned char smem[];
  const uint32_t sbase = smem_u32(smem);
  const uint32_t bars = sbase + RING_BYTES;

  const int tid = threadIdx.x;
  const int wg = __shfl_sync(0xffffffffu, tid >> 7, 0);
  const int cta = blockIdx.x >= NCTA ? blockIdx.x : ((((blockIdx.x >> 1) & 7) * 8 + (blockIdx.x >> 4)) * 2 + (blockIdx.x & 1));
  const int r = cta & 1;
  const int cl = cta >> 1;
  const int j = cl & 7;
  const bool extra = OFF && cta >= NCTA;
  const int rt = (extra ? (cl - 64) * 4 : (cl >> 3)) * 2 + r;
  constexpr int PRE_SLOTS = 9 + (OFF ? 12 : 13) * 9 + 4 * 9 + 5;
  constexpr int PAIR0 = ((PRE_SLOTS % NSLOT) + 1) / 2 % NPAIR;

  if (tid == 256) {
#pragma unroll
    for (int s = 0; s < 9; s++) mbar_init(bars + B_FULL + s * 8, 1);
    asm volatile("fence.mbarrier_init.release.cluster;" ::: "memory");
    asm volatile("fence.proxy.async.shared::cta;" ::: "memory");
#pragma unroll
    for (int kb = 0; kb < 9; kb++) {
      mbar_expect_tx(bars + B_FULL + kb * 8, 16384);
      tma_load(&tm_x, kb * 64, rt * 128, sbase + kb * SLOT_BYTES, bars + B_FULL + kb * 8);
    }
  } else if (tid == 288) {
    asm volatile("prefetch.tensormap [%0];" ::"l"(&tm_wq) : "memory");
#pragma unroll
    for (int s = 9; s < NSLOT; s++) mbar_init(bars + B_FULL + s * 8, 1);
#pragma unroll
    for (int s = 0; s < NSLOT; s++) mbar_init(bars + B_EMPTY + s * 8, 16);
    asm volatile("fence.mbarrier_init.release.cluster;" ::: "memory");
  } else if (tid == 320) {
#pragma unroll
    for (int s = 0; s < NPAIR; s++) {
      mbar_init(bars + B_FULL2 + s * 8, 1);
      mbar_init(bars + B_EMPTY2 + s * 8, 16);
    }
#pragma unroll
    for (int s = 0; s < PAIR0; s++) {
      mbar_arrive(bars + B_FULL2 + s * 8);
      asm volatile("mbarrier.arrive.shared::cta.b64 _, [%0], 16;" ::"r"(bars + B_EMPTY2 + s * 8) : "memory");
    }
    mbar_init(bars + B_DONE, 8);
    mbar_init(bars + B_ZERO, 1);
    mbar_init(bars + B_RED, 8);
    mbar_init(bars + B_MARK, 1);
    mbar_init(bars + B_STG, 8);
    asm volatile("fence.mbarrier_init.release.cluster;" ::: "memory");
  }
  __syncthreads();
  cluster_arrive();
  cluster_wait();

  if (wg == 2) {
    asm volatile("setmaxnreg.dec.sync.aligned.u32 24;");
    const int warp = (tid >> 5) & 3;
    if (warp != 0) cluster_arrive();
    if (warp == 0) {
      if ((tid & 31) == 0) {
        Ring w{9, 0};
        const uint32_t half = r * 8192;
        auto begin = [&](uint32_t bytes) {
          mbar_wait(bars + B_EMPTY + w.slot * 8, w.phase ^ 1);
          mbar_expect_tx(bars + B_FULL + w.slot * 8, bytes);
        };
        uint64_t stream_pol;
        asm volatile("createpolicy.fractional.L2::evict_first.b64 %0, 1.0;" : "=l"(stream_pol));
        auto mc = [&](const CUtensorMap* m, int col, int row, int n, int row_step) {
#pragma unroll 1
          for (int i = 0; i < n; i++) {
            begin(16384);
            tma_load_mc_hint(m, col, row + i * row_step, sbase + w.slot * SLOT_BYTES + half, bars + B_FULL + w.slot * 8, stream_pol);
            w.next();
          }
        };
        if (extra) {
#pragma unroll 1
          for (int job = 0; job < 4; job++) {
#pragma unroll 1
            for (int kb = 0; kb < (job ? 9 : 0); kb++) {
              begin(16384);
              tma_load(&tm_x, kb * 64, (rt + 2 * job) * 128, sbase + w.slot * SLOT_BYTES, bars + B_FULL + w.slot * 8);
              w.next();
            }
#pragma unroll 1
            for (int i = 0; i < 72; i++) {
              begin(16384);
              tma_load_mc(&tm_wq, (4 * (i / 9) + 3) * 128 + r * 64, (i % 9) * 64, sbase + w.slot * SLOT_BYTES + half, bars + B_FULL + w.slot * 8);
              w.next();
            }
#pragma unroll 1
            for (int k = 0; k < 3; k++) { begin(0); w.next(); }
          }
        } else {
#pragma unroll 1
          for (int t = 0; t < (OFF ? 3 : 4); t++) mc(&tm_wq, (4 * j + t) * 128 + r * 64, 0, 9, 64);
#pragma unroll 1
          for (int ch = 0; ch < 9; ch++) mc(r ? &tm_w3 : &tm_w1, j * 576 + ch * 64, 0, 9, 64);
          l2_prefetch(g_qo + (size_t)cta * 4 * 2048, 32768);
#pragma unroll 1
          for (int cc = 0; cc < 4; cc++) {
            mc(&tm_w2, cc * 128 + r * 64, j * 576, 9, 64);
            if (cc == 0) {
              mc(&tm_w2, 512, j * 576 + r * 64, 4, 128);
              begin(8192);
              if (r == 0) tma_load_mc_hint(&tm_w2, 512, j * 576 + 512, sbase + w.slot * SLOT_BYTES, bars + B_FULL + w.slot * 8, stream_pol);
              w.next();
            }
          }
          Ring2 wp{PAIR0, 0};
          bool first_lap = true;
          auto begin2 = [&](uint32_t bytes) {
            if (first_lap) {
#pragma unroll 1
              for (uint32_t s = 2 * wp.slot; s < 2 * wp.slot + 2; s++)
                mbar_wait(bars + B_EMPTY + s * 8, (s < PRE_SLOTS % NSLOT ? PRE_SLOTS / NSLOT : PRE_SLOTS / NSLOT - 1) & 1);
            } else {
              mbar_wait(bars + B_EMPTY2 + wp.slot * 8, wp.phase ^ 1);
            }
            mbar_expect_tx(bars + B_FULL2 + wp.slot * 8, bytes);
          };
          auto end2 = [&]() {
            wp.next();
            if (wp.slot == PAIR0) first_lap = false;
          };
          auto mc2 = [&](const CUtensorMap* m, int col0, int row0, int col1, int row1) {
            begin2(32768);
            const uint32_t fb = bars + B_FULL2 + wp.slot * 8, dst = sbase + wp.slot * 2 * SLOT_BYTES + half;
            tma_load_mc(m, col0, row0, dst, fb);
            tma_load_mc(m, col1, row1, dst + SLOT_BYTES, fb);
            end2();
          };
#pragma unroll 1
          for (int n = 0; n <= 64; n++) {
            if (n < 64) {
              const int row = (2 * j + (n >> 5)) * 2048 + (n & 15) * 128 + r * 64;
              mc2(&tm_k, 0, row, 64, row);
            }
            if (n > 0) {
              const int row = (2 * j + ((n - 1) >> 5)) * 2048 + ((n - 1) & 15) * 128;
              mc2(&tm_v, r * 64, row, r * 64, row + 64);
            }
            if ((n & 15) == 8 && n < (OFF ? 32 : 48)) l2_prefetch(g_qo + (size_t)(cta * 4 + (n >> 4) + 1) * 2048, 32768);
            if (n == 56) {
              l2_prefetch(wog + (size_t)(j * 512 + rt * 32) * 1152, 32 * 1152);
              l2_prefetch(g_qo + (size_t)cta * 4 * 2048, 3 * 32768);
              l2_prefetch(g_S + (size_t)(rt * 72 + j * 9) * 128, 9 * 128 * 16);
            }
          }
#pragma unroll 1
          for (int t = 0; t < 3; t++) {
            begin2(32768);
            bulk_load(sbase + wp.slot * 2 * SLOT_BYTES, g_qo + (size_t)(cta * 4 + t) * 2048, 32768, bars + B_FULL2 + wp.slot * 8);
            end2();
          }
          l2_prefetch(g_G + (size_t)(rt * 72 + j * 9) * 128, 9 * 128 * 16);
          l2_prefetch(x + (size_t)(rt * 128 + j * 16) * DM, 16 * DM * 2);
#pragma unroll 1
          for (int i = 0; i < 16; i++) {
            const int col = s_slice(j, 2 * (i >> 2) + r) * 64, row = j * 512 + (i & 3) * 128;
            mc2(&tm_wo, col, row, col, row + 64);
          }
#pragma unroll 1
          for (int st = 0; st < 2; st++) mc2(&tm_wo, j * 64, j * 512 + st * 256 + r * 64, j * 64, j * 512 + st * 256 + 128 + r * 64);
        }
      }
    } else if (warp == 1 && !extra) {
      const int lane = tid & 31;
      unsigned int epoch = 0;
      if (lane == 0) epoch = ld_acquire(&g_cntD[rt * 32]);
      __nanosleep(5000);
      for (int i = lane; i < 128; i += 32)
        asm volatile("st.shared.v4.u32 [%0], {%1,%1,%1,%1};" ::"r"(bars + B_ZBUF + i * 16), "r"(0) : "memory");
      asm volatile("fence.proxy.async.shared::cta;" ::: "memory");
      __syncwarp();
      if (lane == 0) {
        const uint64_t t0 = gtime();
        auto clear = [&](uint4* buf, unsigned int* cnt) {
          for (int i = 0; i < 9; i++) {
            uint4* dst = buf + (size_t)(rt * 72 + j * 9 + i) * 128;
            asm volatile("cp.async.bulk.global.shared::cta.bulk_group [%0], [%1], 2048;" ::"l"(dst), "r"(bars + B_ZBUF) : "memory");
            __nanosleep(300);
          }
          asm volatile("cp.async.bulk.commit_group;" ::: "memory");
          asm volatile("cp.async.bulk.wait_group 0;" ::: "memory");
          asm volatile("fence.proxy.async.global;" ::: "memory");
          __threadfence();
          atomicAdd(cnt, 8u);
          while ((int)(ld_acquire(cnt) - (epoch + 64)) < 0) {
            __nanosleep(200);
            if (gtime() - t0 > 2000000000ull) __trap();
          }
        };
        clear(g_G, &g_cntZ[rt * 32]);
        mbar_arrive(bars + B_ZERO);
        while (!mbar_try_long(bars + B_STG, 0)) { }
        { const uint64_t t1 = gtime(); while (gtime() - t1 < 30000) __nanosleep(5000); }
        clear(g_S, &g_cntY[rt * 32]);
        if (OFF)
        {
          while ((int)(ld_acquire(&g_cntQ[rt * 32]) - (epoch + 64)) < 0) __nanosleep(2000);
          l2_prefetch(g_qo + (size_t)(cta * 4 + 3) * 2048, 32768);
        }
        mbar_arrive(bars + B_ZERO);
        while (!mbar_test(bars + B_MARK, 0)) __nanosleep(3000);
        while (!mbar_try_long(bars + B_RED, 0)) { }
        asm volatile("fence.acq_rel.gpu;" ::: "memory");
        asm volatile("red.relaxed.gpu.global.add.u32 [%0], 8;" ::"l"(&g_cntD[rt * 32]) : "memory");
        while ((int)(ld_acquire(&g_cntD[rt * 32]) - (epoch + 64)) < 0) { }
        mbar_arrive(bars + B_ZERO);
      }
    } else if (warp == 3) {
      if ((tid & 31) == 0 && !extra) {
        for (int l = 5; l < 14; l++)
          asm volatile("cp.async.bulk.prefetch.tensor.2d.L2.global [%0, {%1, %2}];"
                       ::"l"(&tm_wq), "r"((4 * j + l / 9) * 128 + r * 64), "r"((l % 9) * 64) : "memory");
        asm volatile("prefetch.tensormap [%0];" ::"l"(r ? &tm_w3 : &tm_w1) : "memory");
        asm volatile("prefetch.tensormap [%0];" ::"l"(&tm_w2) : "memory");
        asm volatile("prefetch.tensormap [%0];" ::"l"(&tm_k) : "memory");
        asm volatile("prefetch.tensormap [%0];" ::"l"(&tm_v) : "memory");
        asm volatile("prefetch.tensormap [%0];" ::"l"(&tm_wo) : "memory");
      }
    } else if (warp == 2) {
      if ((tid & 31) == 0) {
        if (sbase & 1023) __trap();
        const uint64_t t0 = gtime();
        while (!mbar_test(bars + B_MARK, 0)) {
          __nanosleep(3000);
          if (gtime() - t0 > 2000000000ull) __trap();
        }
        while (!mbar_try_long(bars + B_DONE, 0)) {
          if (gtime() - t0 > 2000000000ull) __trap();
        }
      }
    }
    __syncwarp();
    if (warp == 0) cluster_arrive();
    cluster_wait();
  } else {
    asm volatile("setmaxnreg.inc.sync.aligned.u32 240;");
    Ctx c;
    c.ring = sbase;
    c.bars = bars;
    c.rel = mapa(bars, tid & 1);
    c.rel_lane = (tid & 31) < 2;
    c.wg = wg;
    c.rd = Ring{0, 0};
    c.rp = Ring2{PAIR0, 0};
    if (wg == 1) bar_arrive(1, 256);

    float acc[64];
    auto qo_ptr = [&](int tile) { return g_qo + (ptrdiff_t)((cta * 4 + tile) * 2 + wg) * 1024 + (fresh_tid() & 127); };

    uint32_t q[32];
    auto load_q = [&](int tile) {
      const uint4* src = qo_ptr(tile);
#pragma unroll
      for (int i = 0; i < 8; i++) {
        const uint4 v = __ldcg(src + i * 128);
        q[4 * i] = v.x; q[4 * i + 1] = v.y; q[4 * i + 2] = v.z; q[4 * i + 3] = v.w;
      }
    };
    {
      uint32_t a[144];
      float rs0, rs1;
#pragma unroll 1
      for (int job = 0;; job++) {
      {
        const int lane = tid & 31, warp = (tid >> 5) & 3;
        const int row = warp * 16 + (lane & 7) + ((lane >> 3) & 1) * 8;
        const uint32_t rowoff = wg * 8192 + row * 128;
        float sm[2][4], sq[4][4];
#pragma unroll
        for (int u = 0; u < 4; u++) { sm[0][u] = 0.f; sm[1][u] = 0.f; sq[0][u] = 0.f; sq[1][u] = 0.f; sq[2][u] = 0.f; sq[3][u] = 0.f; }
        auto gram = [&](int i) {
          const int u = (i >> 2) & 1;
          mma16816(sq[u][0], sq[u][1], sq[u][2], sq[u][3], a[i], a[i + 1], a[i + 2], a[i + 3], a[i], a[i + 2]);
          mma16816(sq[u + 2][0], sq[u + 2][1], sq[u + 2][2], sq[u + 2][3], a[i], a[i + 1], a[i + 2], a[i + 3], a[i + 1], a[i + 3]);
        };
        const int g = lane >> 2;
        auto diag = [&](float& q0, float& q1) {
          q0 = __shfl_sync(0xffffffffu, (g & 1) ? sq[0][1] + sq[1][1] : sq[0][0] + sq[1][0], g * 4 + (g >> 1)) * (1.f / DM);
          q1 = __shfl_sync(0xffffffffu, (g & 1) ? sq[2][3] + sq[3][3] : sq[2][2] + sq[3][2], g * 4 + (g >> 1)) * (1.f / DM);
        };
#pragma unroll
        for (int kb = 0; kb < 9; kb++) {
          mbar_wait(bars + B_FULL + kb * 8, 0);
          const uint32_t sb = c.ring + kb * SLOT_BYTES + rowoff;
#pragma unroll
          for (int ks = 0; ks < 4; ks++) {
            const uint32_t addr = sb + (((2 * ks + (lane >> 4)) ^ (lane & 7)) << 4);
            const int i = kb * 16 + ks * 4;
            asm volatile("ldmatrix.sync.aligned.m8n8.x4.shared.b16 {%0,%1,%2,%3}, [%4];"
                         : "=r"(a[i]), "=r"(a[i + 1]), "=r"(a[i + 2]), "=r"(a[i + 3]) : "r"(addr) : "memory");
          }
          __syncwarp();
          c.release(kb);
#pragma unroll
          for (int ks = 0; ks < 4; ks++) {
            const int i = kb * 16 + ks * 4;
            mma16816(sm[ks & 1][0], sm[ks & 1][1], sm[ks & 1][2], sm[ks & 1][3], a[i], a[i + 1], a[i + 2], a[i + 3], 0x3f803f80u, 0x3f803f80u);
            gram(i);
          }
        }
        c.rd.slot = 9;
        const float mean0 = (sm[0][0] + sm[1][0]) * (1.f / DM), mean1 = (sm[0][2] + sm[1][2]) * (1.f / DM);
        const __nv_bfloat162 m0 = __float2bfloat162_rn(mean0), m1 = __float2bfloat162_rn(mean1);
#pragma unroll
        for (int i = 0; i < 144; i += 2) {
          __nv_bfloat162 u = __hsub2(*reinterpret_cast<__nv_bfloat162*>(&a[i]), m0);
          __nv_bfloat162 v = __hsub2(*reinterpret_cast<__nv_bfloat162*>(&a[i + 1]), m1);
          a[i] = *reinterpret_cast<uint32_t*>(&u);
          a[i + 1] = *reinterpret_cast<uint32_t*>(&v);
        }
        float q0, q1;
        diag(q0, q1);
        float var0 = q0 - mean0 * mean0, var1 = q1 - mean1 * mean1;
        if (__any_sync(0xffffffffu, !(var0 > q0 * (1.f / 256.f)) || !(var1 > q1 * (1.f / 256.f)))) {
#pragma unroll
          for (int u = 0; u < 4; u++) { sq[0][u] = 0.f; sq[1][u] = 0.f; sq[2][u] = 0.f; sq[3][u] = 0.f; }
#pragma unroll
          for (int i = 0; i < 144; i += 4) gram(i);
          diag(q0, q1);
          const float e0 = mean0 - __low2float(m0), e1 = mean1 - __low2float(m1);
          var0 = fmaxf(q0 - e0 * e0, 0.f);
          var1 = fmaxf(q1 - e1 * e1, 0.f);
        }
        rs0 = rcp(bf_round(sqrt_ap(bf_round(bf_round(var0) + 1e-5f))));
        rs1 = rcp(bf_round(sqrt_ap(bf_round(bf_round(var1) + 1e-5f))));
      }
      pin(a);
      const float LOG2E = 1.4426950408889634f;
      uint4* const hs = g_h + (size_t)(cta * 2 + wg) * 36 * 128 + (tid & 127);
      auto swiglu = [&](uint32_t* h) {
        const float ne0 = -rs0 * LOG2E, ne1 = -rs1 * LOG2E, rr0 = rs0 * rs0, rr1 = rs1 * rs1;
#pragma unroll
        for (int i = 0; i < 16; i++) {
          const float ne = (i & 1) ? ne1 : ne0, rr = (i & 1) ? rr1 : rr0;
          const float g0 = acc[2 * i], g1 = acc[2 * i + 1];
          const float h0 = g0 * acc[32 + 2 * i] * rr * rcp(1.f + ex2(g0 * ne));
          const float h1 = g1 * acc[33 + 2 * i] * rr * rcp(1.f + ex2(g1 * ne));
          h[i] = pack2(h0, h1);
        }
      };
      uint4* const Gd = g_G + (size_t)(rt * 2 + wg) * 36 * 128 + (tid & 127);
#pragma unroll 1
      for (int ch = extra ? -8 : (OFF ? 1 : 0); ch < (extra ? 0 : 18); ch++) {
        if (ch == 14) gemm_n64(c, acc, a);
        else gemm_n128(c, acc, a, ch == 12 ? hs : qo_ptr(0), ch == 12 ? 8 : (ch == 17 ? 2 : 0));
        if (ch < 4) {
          uint4* dst = qo_ptr(extra ? (((((rt >> 1) + job) * 8 + ch + 8) * 2 + r) - cta) * 4 + 3 : ch - (OFF ? 1 : 0));
#pragma unroll
          for (int i = 0; i < 8; i++) {
            __stcs(dst + i * 128,
                   make_uint4(pack2(acc[8 * i] * rs0, acc[8 * i + 1] * rs0), pack2(acc[8 * i + 2] * rs1, acc[8 * i + 3] * rs1),
                              pack2(acc[8 * i + 4] * rs0, acc[8 * i + 5] * rs0), pack2(acc[8 * i + 6] * rs1, acc[8 * i + 7] * rs1)));
          }
        } else if (ch < 13) {
          uint32_t h[16];
          swiglu(h);
          if (ch < 12) {
#pragma unroll
            for (int i = 0; i < 4; i++) hs[((ch - 4) * 4 + i) * 128] = make_uint4(h[4 * i], h[4 * i + 1], h[4 * i + 2], h[4 * i + 3]);
          } else {
#pragma unroll
            for (int i = 0; i < 16; i++) a[128 + i] = h[i];
            mbar_wait(bars + B_ZERO, 0);
          }
        } else if (ch == 14) {
          red_out<8>(Gd + 32 * 128, acc);
        } else if (ch < 17) {
          red_out<16>(Gd + (ch == 13 ? 0 : ch - 14) * 8 * 128, acc);
        }
        pin(a);
      }
      if (!extra) break;
      asm volatile("fence.acq_rel.gpu;" ::: "memory");
      __syncwarp();
      if ((tid & 31) == 0) asm volatile("red.relaxed.gpu.global.add.u32 [%0], 8;" ::"l"(&g_cntQ[(rt + 2 * job) * 32]) : "memory");
      for (int k = 0; k < 3; k++) { c.wait_full(); c.release(c.rd.slot); c.rd.next(); }
      if (job == 3) {
        if (wg == 0) c.turn_wait();
        if (tid == 0) mbar_arrive(bars + B_MARK);
        if ((tid & 31) == 0) mbar_arrive(bars + B_DONE);
        __syncwarp();
        asm volatile("barrier.cluster.arrive.release.aligned;" ::: "memory");
        cluster_wait();
        return;
      }
      }
#pragma unroll
      for (int i = 0; i < 32; i++) q[i] = a[i];
    }

    uint32_t ao[128];
    float o[64];
    {
      const float SC = 0.08838834764831845f * 1.4426950408889634f;
      uint32_t p[32] = {};
      float l0, l1;
      pin(q);
      auto issue_qk = [&](float (&acc)[64], uint32_t st) {
        const uint64_t d0 = DESC_K | (c.ring_lo() + st * (2 * SLOT_BYTES >> 4));
        mma_n128<0, 0>(acc, q[0], q[1], q[2], q[3], d0);
#pragma unroll
        for (int ks = 1; ks < 8; ks++)
          mma_n128<0, 1>(acc, q[4 * ks], q[4 * ks + 1], q[4 * ks + 2], q[4 * ks + 3], d0 + (ks >> 2) * (SLOT_BYTES >> 4) + (ks & 3) * 2);
        wg_commit();
      };
      auto issue_pv = [&](uint32_t st, int accumulate) {
        const uint64_t d0 = DESC_MN | (c.ring_lo() + st * (2 * SLOT_BYTES >> 4));
        mma_n128_p<1>(o, p[0], p[1], p[2], p[3], d0, accumulate);
#pragma unroll
        for (int ks = 1; ks < 8; ks++)
          mma_n128<1, 1>(o, p[4 * ks], p[4 * ks + 1], p[4 * ks + 2], p[4 * ks + 3], d0 + (ks >> 2) * (SLOT_BYTES >> 4) + (ks & 3) * 128);
        wg_commit();
      };
      const float LIM = 65536.f;
      float b0, b1, s0, s1;
      auto row_max = [&](float (&acc)[64], float& x0, float& x1) {
        float xa[4], xb[4];
#pragma unroll
        for (int u = 0; u < 4; u++) {
          xa[u] = fmaxf(acc[4 * u], acc[4 * u + 1]);
          xb[u] = fmaxf(acc[4 * u + 2], acc[4 * u + 3]);
        }
#pragma unroll
        for (int n = 4; n < 16; n++) {
          xa[n & 3] = fmaxf(xa[n & 3], acc[4 * n]);
          xb[n & 3] = fmaxf(xb[n & 3], acc[4 * n + 2]);
          xa[(n + 2) & 3] = fmaxf(xa[(n + 2) & 3], acc[4 * n + 1]);
          xb[(n + 2) & 3] = fmaxf(xb[(n + 2) & 3], acc[4 * n + 3]);
        }
        x0 = quad_max(fmaxf(fmaxf(xa[0], xa[1]), fmaxf(xa[2], xa[3])));
        x1 = quad_max(fmaxf(fmaxf(xb[0], xb[1]), fmaxf(xb[2], xb[3])));
      };
      auto first_ref = [&](float (&acc)[64]) {
        const float x0 = fmaxf(fmaxf(fmaxf(acc[0], acc[1]), fmaxf(acc[4], acc[5])), fmaxf(fmaxf(acc[8], acc[9]), fmaxf(acc[12], acc[13])));
        const float x1 = fmaxf(fmaxf(fmaxf(acc[2], acc[3]), fmaxf(acc[6], acc[7])), fmaxf(fmaxf(acc[10], acc[11]), fmaxf(acc[14], acc[15])));
        b0 = quad_max(x0) * -SC;
        b1 = quad_max(x1) * -SC;
      };
      auto sm_exp = [&](float (&acc)[64], int n0, int n1, float c0, float c1) {
        if (n0 == 0) { s0 = 0.f; s1 = 0.f; }
#pragma unroll
        for (int n = 0; n < 16; n++) {
          if (n >= n0 && n < n1) {
            acc[4 * n] = ex2(fmaf(acc[4 * n], SC, c0));
            acc[4 * n + 1] = ex2(fmaf(acc[4 * n + 1], SC, c0));
            acc[4 * n + 2] = ex2(fmaf(acc[4 * n + 2], SC, c1));
            acc[4 * n + 3] = ex2(fmaf(acc[4 * n + 3], SC, c1));
            s0 += acc[4 * n] + acc[4 * n + 1];
            s1 += acc[4 * n + 2] + acc[4 * n + 3];
          }
        }
      };
      auto pack_p = [&](float (&acc)[64]) {
#pragma unroll
        for (int i = 0; i < 32; i++) p[i] = pack2(acc[2 * i], acc[2 * i + 1]);
      };

      float f0 = 0.f, f1 = 0.f;
      {
        uint4* const Gd = g_G + (size_t)((rt * 2 + wg) * 36 + 24) * 128 + (fresh_tid() & 127);
        if (wg == 0) red_out<16>(Gd, acc);
        c.wait_full2();
        c.turn_wait();
        wg_fence();
        issue_qk(o, PAIR0);
        c.turn_pass();
        if (wg == 1) red_out<16>(Gd, acc);
        __syncwarp();
        if ((fresh_tid() & 31) == 0) mbar_arrive(bars + B_STG);
      }
      wg_wait<0>();
      pin(o);
      first_ref(o);
#pragma unroll
      for (int i = 0; i < 64; i++) acc[i] = o[i];
      auto first_half = [&]() {
        sm_exp(acc, 0, SPLIT, b0, b1);
#pragma unroll
        for (int i = SPLIT; i < 16; i++) {
          acc[4 * i] = fmaf(acc[4 * i], SC, b0);
          acc[4 * i + 1] = fmaf(acc[4 * i + 1], SC, b0);
          acc[4 * i + 2] = fmaf(acc[4 * i + 2], SC, b1);
          acc[4 * i + 3] = fmaf(acc[4 * i + 3], SC, b1);
        }
      };
      first_half();
      l0 = 0.f; l1 = 0.f;
      Ring2 ks = c.rp, vs = c.rp;
      uint32_t ready;
#pragma unroll 1
      for (int n = -1;; n++) {
        const bool boundary = (n & 15) == 15 && n > 0;
        const bool newq = (n & 15) == 14 && n < 48;
        wg_wait<0>();
        pin(o); pin(acc);
        const uint32_t kcur = ks.slot;
        if (n >= 0) c.release2(vs.slot);
        ks = vs; ks.next();
        vs = ks; vs.next();
        ready = mbar_test2(bars + B_FULL2 + ks.slot * 8, ks.phase, bars + B_FULL2 + vs.slot * 8, vs.phase);
#pragma unroll
        for (int i = SPLIT; i < 16; i++) {
          acc[4 * i] = ex2(acc[4 * i]);
          acc[4 * i + 1] = ex2(acc[4 * i + 1]);
          acc[4 * i + 2] = ex2(acc[4 * i + 2]);
          acc[4 * i + 3] = ex2(acc[4 * i + 3]);
          s0 += acc[4 * i] + acc[4 * i + 1];
          s1 += acc[4 * i + 2] + acc[4 * i + 3];
        }
        pack_p(acc);
        const bool bad = !(s0 <= LIM) || !(s1 <= LIM);
        if (__any_sync(0xffffffffu, bad || !ready || boundary || n == 62)) {
        if (boundary) {
          uint4* dst = qo_ptr(n >> 4);
#pragma unroll
          for (int i = 0; i < 8; i++)
            dst[i * 128] = make_uint4(pack2(o[8 * i] * f0, o[8 * i + 1] * f0), pack2(o[8 * i + 2] * f1, o[8 * i + 3] * f1),
                                      pack2(o[8 * i + 4] * f0, o[8 * i + 5] * f0), pack2(o[8 * i + 6] * f1, o[8 * i + 7] * f1));
        }
        if (__any_sync(0xffffffffu, bad)) {
          if (newq) load_q(n >> 4);
          const int lane = fresh_tid() & 31;
          uint32_t kb = c.ring + kcur * 2 * SLOT_BYTES + (lane & 7) * 128;
#pragma unroll
          for (int nb = 0; nb < 16; nb++) {
            if (nb > 0) kb += __float_as_uint(acc[4 * nb - 4]) & (blockDim.y - 1);
            acc[4 * nb] = 0.f; acc[4 * nb + 1] = 0.f; acc[4 * nb + 2] = 0.f; acc[4 * nb + 3] = 0.f;
#pragma unroll
            for (int kp = 0; kp < 4; kp++) {
              uint32_t r0, r1, r2, r3;
              const uint32_t addr = kb + (kp >> 1) * SLOT_BYTES + nb * 1024 + ((((kp & 1) * 4 + (lane >> 3)) ^ (lane & 7)) << 4);
              asm volatile("ldmatrix.sync.aligned.m8n8.x4.shared.b16 {%0,%1,%2,%3}, [%4];"
                           : "=r"(r0), "=r"(r1), "=r"(r2), "=r"(r3) : "r"(addr) : "memory");
              mma16816(acc[4 * nb], acc[4 * nb + 1], acc[4 * nb + 2], acc[4 * nb + 3], q[8 * kp], q[8 * kp + 1], q[8 * kp + 2], q[8 * kp + 3], r0, r1);
              mma16816(acc[4 * nb], acc[4 * nb + 1], acc[4 * nb + 2], acc[4 * nb + 3], q[8 * kp + 4], q[8 * kp + 5], q[8 * kp + 6], q[8 * kp + 7], r2, r3);
            }
          }
          float x0, x1;
          row_max(acc, x0, x1);
          if (newq) load_q((n >> 4) + 1 + (__float_as_uint(x0) & (blockDim.y - 1)));
          x0 = fminf(-x0 * SC, b0); x1 = fminf(-x1 * SC, b1);
          f0 = ex2(x0 - b0); f1 = ex2(x1 - b1);
          b0 = x0; b1 = x1;
          l0 *= f0; l1 *= f1;
#pragma unroll
          for (int i = 0; i < 16; i++) {
            o[4 * i] *= f0; o[4 * i + 1] *= f0; o[4 * i + 2] *= f1; o[4 * i + 3] *= f1;
          }
          sm_exp(acc, 0, 16, b0, b1);
          pack_p(acc);
          __syncwarp();
        }
        if (n == 62) {
          c.release2(kcur);
          l0 += s0; l1 += s1;
          break;
        }
        mbar_wait(bars + B_FULL2 + ks.slot * 8, ks.phase);
        mbar_wait(bars + B_FULL2 + vs.slot * 8, vs.phase);
        }
        pin(p); pin(q); pin(o);
        c.turn_wait();
        wg_fence();
        issue_qk(acc, ks.slot);
        issue_pv(vs.slot, (n & 15) != 15);
        c.turn_pass();
        c.release2(kcur);
        l0 += s0; l1 += s1;
        wg_wait<1>();
        pin(acc);
        if (((n + 4) & 15) < 3) {
          if ((n & 15) == 12) {
            asm volatile("fence.proxy.async.global;" ::: "memory");
            __syncwarp();
          } else if ((n & 15) == 13) {
            if (n == 45) mbar_wait(bars + B_ZERO, 1);
            if (n < 48) load_q((n >> 4) + 1);
          } else {
            first_ref(acc);
            f0 = rcp(quad_sum(l0));
            f1 = rcp(quad_sum(l1));
            l0 = 0.f; l1 = 0.f;
          }
        }
        first_half();
      }
      mbar_wait(bars + B_FULL2 + ks.slot * 8, ks.phase);
      pin(p); pin(o);
      c.turn_wait();
      wg_fence();
      issue_pv(ks.slot, 1);
      c.turn_pass();
      c.rp = vs;
      {
        const uint32_t off = wg * 16384 + (fresh_tid() & 127) * 16;
#pragma unroll
        for (int t = 0; t < 3; t++) {
          c.wait_full2();
          const uint32_t src = c.ring + c.rp.slot * 2 * SLOT_BYTES + off;
#pragma unroll
          for (int i = 0; i < 8; i++) {
            const int e = t * 32 + i * 4;
            asm volatile("ld.shared.v4.u32 {%0,%1,%2,%3}, [%4];"
                         : "=r"(ao[e]), "=r"(ao[e + 1]), "=r"(ao[e + 2]), "=r"(ao[e + 3]) : "r"(src + i * 2048) : "memory");
          }
          __syncwarp();
          c.release2(c.rp.slot);
          c.rp.next();
        }
      }
      f0 = rcp(quad_sum(l0));
      f1 = rcp(quad_sum(l1));
      wg_wait<0>();
      pin(o);
      c.release2(ks.slot);
#pragma unroll
      for (int i = 0; i < 16; i++) {
        ao[96 + 2 * i] = pack2(o[4 * i] * f0, o[4 * i + 1] * f0);
        ao[97 + 2 * i] = pack2(o[4 * i + 2] * f1, o[4 * i + 3] * f1);
      }
    }
    pin(ao);
    const int tid2 = fresh_tid();
    if (tid2 == 0) mbar_arrive(bars + B_MARK);
    uint4* const Sd = g_S + (size_t)(rt * 2 + wg) * 36 * 128 + (tid2 & 127);
    uint32_t spare = 0;
#pragma unroll 1
    for (int cc = 0; cc < 4; cc++) {
      spare = c.rp.slot;
      gemm_s(c, o, ao, cc < 2 ? 4 : (cc == 2 ? 3 : 0));
      uint4* const d0 = Sd + s_slice(j, 2 * cc) * 4 * 128;
      uint4* const d1 = Sd + s_slice(j, 2 * cc + 1) * 4 * 128;
#pragma unroll
      for (int n = 0; n < 4; n++) red8(d0 + n * 128, &o[8 * n]);
#pragma unroll
      for (int n = 4; n < 8; n++) red8(d1 + (n - 4) * 128, &o[8 * n]);
    }
    __syncwarp();
    if ((tid2 & 31) == 0) mbar_arrive(bars + B_RED);
    {
      const int lane = tid2 & 31, warp = (tid2 >> 5) & 3;
      const int row = rt * 128 + wg * 64 + warp * 16 + (lane >> 2);
      uint32_t* op = reinterpret_cast<uint32_t*>(out + (size_t)row * DM + (lane & 3) * 2);
      uint32_t xa[9], xb[9], ga[9], gb[9];
      auto load9 = [&](const uint4* src, uint32_t* va, uint32_t* vb) {
#pragma unroll
        for (int i = 0; i < 4; i++) {
          const uint4 v = __ldcg(src + (4 * j + i) * 128);
          va[2 * i] = v.x; vb[2 * i] = v.y; va[2 * i + 1] = v.z; vb[2 * i + 1] = v.w;
        }
        const uint2 v = __ldcg(reinterpret_cast<const uint2*>(src + (32 + (j >> 1)) * 128) + (j & 1));
        va[8] = v.x; vb[8] = v.y;
      };
      load9(g_G + (size_t)(rt * 2 + wg) * 36 * 128 + (tid2 & 127), ga, gb);
      {
        const uint32_t* xp = reinterpret_cast<const uint32_t*>(x + (size_t)row * DM + (lane & 3) * 2);
#pragma unroll
        for (int i = 0; i < 9; i++) {
          const int e = (i < 8 ? 8 * j + i : 64 + j) * 4;
          xa[i] = __ldg(xp + e);
          xb[i] = __ldg(xp + e + 8 * DM / 2);
        }
      }
      {
        c.wait_full2();
        const uint64_t db0 = DESC_MN | (c.ring_lo() + c.rp.slot * (2 * SLOT_BYTES >> 4));
        c.rp.next();
        c.wait_full2();
        const uint64_t db1 = DESC_MN | (c.ring_lo() + c.rp.slot * (2 * SLOT_BYTES >> 4));
        cluster_arrive();
        c.turn_wait();
        wg_fence();
#pragma unroll
        for (int ks = 0; ks < 32; ks++) {
          const uint64_t d = (ks < 16 ? db0 : db1) + (ks & 15) * 128;
          if (ks == 0) mma_n64<0>(o, ao[0], ao[1], ao[2], ao[3], d);
          else mma_n64<1>(o, ao[4 * ks], ao[4 * ks + 1], ao[4 * ks + 2], ao[4 * ks + 3], d);
        }
        wg_commit();
        if (wg == 0) c.turn_pass();
      }
      auto silu2 = [&](uint32_t g2) {
        const float g_lo = bf_lo(g2), g_hi = bf_hi(g2);
        return pack2(g_lo * rcp(1.f + ex2(-g_lo * 1.4426950408889634f)), g_hi * rcp(1.f + ex2(-g_hi * 1.4426950408889634f)));
      };
#pragma unroll
      for (int i = 0; i < 9; i++) { ga[i] = silu2(ga[i]); gb[i] = silu2(gb[i]); }
      uint32_t dep = 0;
#pragma unroll
      for (int i = 0; i < 9; i++) dep ^= ga[i] ^ gb[i] ^ xa[i] ^ xb[i];
      mbar_wait(bars + B_ZERO, dep & (blockDim.y - 1));
      uint32_t sa[9], sb[9];
      load9(Sd, sa, sb);
      wg_wait<0>();
#pragma unroll
      for (int i = 0; i < 32; i++) asm volatile("" : "+f"(o[i])::"memory");
      auto fin2 = [&](uint32_t x2, uint32_t s2, uint32_t g2) {
        uint32_t u2;
        asm("mul.rn.bf16x2 %0, %1, %2;" : "=r"(u2) : "r"(s2), "r"(g2));
        asm("add.rn.bf16x2 %0, %1, %2;" : "=r"(u2) : "r"(x2), "r"(u2));
        return u2;
      };
      uint32_t ra[9], rb[9];
#pragma unroll
      for (int i = 0; i < 9; i++) {
        if (i < 8) {
          sa[i] = pack2(bf_lo(sa[i]) + o[4 * i], bf_hi(sa[i]) + o[4 * i + 1]);
          sb[i] = pack2(bf_lo(sb[i]) + o[4 * i + 2], bf_hi(sb[i]) + o[4 * i + 3]);
        }
        ra[i] = fin2(xa[i], sa[i], ga[i]);
        rb[i] = fin2(xb[i], sb[i], gb[i]);
      }
      op[(64 + j) * 4] = ra[8];
      op[(64 + j) * 4 + 8 * DM / 2] = rb[8];
      const uint32_t tb = c.ring + spare * 2 * SLOT_BYTES + (wg * 4 + warp) * 2048;
      {
        const int mrow = (lane & 7) + ((lane >> 3) & 1) * 8;
#pragma unroll
        for (int u = 0; u < 4; u++) {
          const uint32_t addr = tb + mrow * 128 + (((2 * u + (lane >> 4)) ^ (lane & 7)) << 4);
          asm volatile("stmatrix.sync.aligned.m8n8.x4.shared.b16 [%0], {%1,%2,%3,%4};"
                       ::"r"(addr), "r"(ra[2 * u]), "r"(rb[2 * u]), "r"(ra[2 * u + 1]), "r"(rb[2 * u + 1]) : "memory");
        }
        __syncwarp();
        uint4* const orow = reinterpret_cast<uint4*>(out + (size_t)(rt * 128 + wg * 64 + warp * 16 + (lane >> 3)) * DM + j * 64) + (lane & 7);
#pragma unroll
        for (int u = 0; u < 4; u++) {
          const int rr = u * 4 + (lane >> 3);
          uint4 v;
          asm volatile("ld.shared.v4.u32 {%0,%1,%2,%3}, [%4];"
                       : "=r"(v.x), "=r"(v.y), "=r"(v.z), "=r"(v.w) : "r"(tb + rr * 128 + (((lane & 7) ^ (rr & 7)) << 4)) : "memory");
          orow[u * 4 * DM / 8] = v;
        }
      }
      if (lane == 0) mbar_arrive(bars + B_DONE);
    }
    __syncwarp();
    cluster_wait();
  }
}

typedef CUresult (*EncodeFn)(CUtensorMap*, CUtensorMapDataType, cuuint32_t, void*, const cuuint64_t*, const cuuint64_t*,
                             const cuuint32_t*, const cuuint32_t*, CUtensorMapInterleave, CUtensorMapSwizzle,
                             CUtensorMapL2promotion, CUtensorMapFloatOOBfill);

static void make_map(EncodeFn enc, CUtensorMap* m, const void* ptr, uint64_t rows, uint64_t cols, uint32_t box_rows = 64) {
  cuuint64_t dims[2] = {cols, rows};
  cuuint64_t strides[1] = {cols * 2};
  cuuint32_t box[2] = {64, box_rows};
  cuuint32_t es[2] = {1, 1};
  enc(m, CU_TENSOR_MAP_DATA_TYPE_BFLOAT16, 2, const_cast<void*>(ptr), dims, strides, box, es, CU_TENSOR_MAP_INTERLEAVE_NONE,
      CU_TENSOR_MAP_SWIZZLE_128B, CU_TENSOR_MAP_L2_PROMOTION_L2_128B, CU_TENSOR_MAP_FLOAT_OOB_FILL_NONE);
}

}

extern "C" void kernel_launch(void* const* d_in, const int* in_sizes, int n_in, void* d_out, int out_size) {
  using namespace fk;
  (void)in_sizes; (void)n_in; (void)out_size;
  static EncodeFn enc = nullptr;
  static bool off = false;
  if (!enc) {
    void* fn = nullptr;
    cudaDriverEntryPointQueryResult st;
    cudaGetDriverEntryPoint("cuTensorMapEncodeTiled", &fn, cudaEnableDefault, &st);
    enc = (EncodeFn)fn;
    cudaFuncSetAttribute(fused_kernel<false>, cudaFuncAttributeMaxDynamicSharedMemorySize, SMEM_BYTES);
    cudaFuncSetAttribute(fused_kernel<true>, cudaFuncAttributeMaxDynamicSharedMemorySize, SMEM_BYTES);
    cudaLaunchConfig_t cfg = {};
    cfg.gridDim = dim3(NCTA + 4);
    cfg.blockDim = dim3(384);
    cfg.dynamicSmemBytes = SMEM_BYTES;
    cudaLaunchAttribute at;
    at.id = cudaLaunchAttributeClusterDimension;
    at.val.clusterDim.x = 2; at.val.clusterDim.y = 1; at.val.clusterDim.z = 1;
    cfg.attrs = &at;
    cfg.numAttrs = 1;
    int ncl = 0;
    off = cudaOccupancyMaxActiveClusters(&ncl, fused_kernel<true>, &cfg) == cudaSuccess && ncl >= NCTA / 2 + 2;
    (void)cudaGetLastError();
  }
  CUtensorMap mx, mw1, mw3, mwq, mw2, mk, mv, mwo;
  make_map(enc, &mx, d_in[0], SEQ, DM, 128);
  make_map(enc, &mk, d_in[1], 16 * SEQ, 128);
  make_map(enc, &mv, d_in[2], 16 * SEQ, 128);
  make_map(enc, &mwq, d_in[3], DM, 4096);
  make_map(enc, &mwo, d_in[4], 4096, DM);
  make_map(enc, &mw1, d_in[6], DM, FF);
  make_map(enc, &mw3, d_in[7], DM, FF);
  make_map(enc, &mw2, d_in[8], FF, DM);
  auto kern = off ? fused_kernel<true> : fused_kernel<false>;
  kern<<<off ? NCTA + 4 : NCTA, 384, SMEM_BYTES>>>(mx, mw1, mw3, mwq, mw2, mk, mv, mwo, (const __nv_bfloat16*)d_in[0],
                                                   (__nv_bfloat16*)d_out, (const char*)d_in[4]);
}
```
